```python
import torch

def _softmax(x, axis=-1):
    return torch.softmax(x, dim=axis)
def _gelu(x):
    return torch.nn.functional.gelu(x, approximate="tanh")
def _silu(x):
    return torch.nn.functional.silu(x)
def _sigmoid(x):
    return torch.sigmoid(x)
def _layernorm(x, axis=-1, eps=1e-5):
    m = x.mean(dim=axis, keepdim=True)
    v = x.var(dim=axis, keepdim=True, unbiased=False)
    return (x - m) / torch.sqrt(v + eps)
def _scatter_add(tgt, idx, src, axis=0):
    return tgt.clone().index_add_(axis, idx, src)
def _segment_sum(src, seg, n):
    out = torch.zeros((n,) + src.shape[1:], dtype=src.dtype)
    return out.index_add_(0, seg, src)
def _pad(x, pw):
    flat = tuple(v for pair in reversed(pw) for v in pair)
    return torch.nn.functional.pad(x, flat)

kernel_name = 'interleave_layers__sliding_block_cached__glu_gated_swiglu__decode'

def setup_inputs():

    _w = (lambda a: (lambda t: t.to(torch.bfloat16) if t.is_floating_point() else t)(torch.as_tensor(a)))
    def _A_setup():
        B, Sq, D = 1, 1, 512
        Hq, Hkv, Sk, Dh = 32, 8, 32768, 128
        assert Hq % Hkv == 0, (Hq, Hkv)
        return {
            "x": _w((lambda *s: torch.randn(*s, dtype=torch.bfloat16) * 0.05)(B, Sq, D)),
            "k_cache": _w((lambda *s: torch.randn(*s, dtype=torch.bfloat16) * 0.8)(B, Hkv, Sk, Dh)),
            "v_cache": _w((lambda *s: torch.randn(*s, dtype=torch.bfloat16) * 0.8)(B, Hkv, Sk, Dh)),
            "wq": _w((lambda *s: torch.randn(*s, dtype=torch.bfloat16) * 0.8)(D, Hq * Dh) * (D ** -0.5)),
            "wo": _w((lambda *s: torch.randn(*s, dtype=torch.bfloat16) * 0.8)(Hq * Dh, D) * ((Hq * Dh) ** -0.5)),
        }
    _A_in = _A_setup()

    def _B_setup():
        B, S, D, F = 1, 1, 512, 1792
        return {
            "x": _w((lambda *s: torch.randn(*s, dtype=torch.bfloat16) * 0.05)(B, S, D)),
            "w1": _w((lambda *s: torch.randn(*s, dtype=torch.bfloat16) * 0.2)(D, F) * (2.0 / D) ** 0.5),
            "w3": _w((lambda *s: torch.randn(*s, dtype=torch.bfloat16) * 0.2)(D, F) * (2.0 / D) ** 0.5),
            "w2": _w((lambda *s: torch.randn(*s, dtype=torch.bfloat16) * 0.2)(F, D) * (2.0 / F) ** 0.5),
        }
    _B_in = _B_setup()

    return {
        "A_x": _A_in["x"],
        "A_k_cache": _A_in["k_cache"],
        "A_v_cache": _A_in["v_cache"],
        "A_wq": _A_in["wq"],
        "A_wo": _A_in["wo"],
        "B_x": _B_in["x"],
        "B_w1": _B_in["w1"],
        "B_w3": _B_in["w3"],
        "B_w2": _B_in["w2"],
    }

def reference(A_x, A_k_cache, A_v_cache, A_wq, A_wo, B_x, B_w1, B_w3, B_w2):
    def _A_ref(x, k_cache, v_cache, wq, wo):
        B, Sq, D = x.shape
        Hq, Dh = 32, 128
        Hkv, Sk = k_cache.shape[1], k_cache.shape[2]
        W = min(4096, max(256, Sk // 4))
        rep = Hq // Hkv
        q = (lambda x, *d: x.permute(*d))((x @ wq).reshape(B, Sq, Hq, Dh), 0, 2, 1, 3)
        k = (lambda x, n, axis: torch.repeat_interleave(x, n, dim=axis))(k_cache[:, :, Sk - W:, :], rep, axis=1)
        v = (lambda x, n, axis: torch.repeat_interleave(x, n, dim=axis))(v_cache[:, :, Sk - W:, :], rep, axis=1)
        scores = torch.einsum("bhqd,bhkd->bhqk", q, k) * (Dh ** -0.5)
        p = _softmax(scores, axis=-1)
        o = torch.einsum("bhqk,bhkd->bhqd", p, v)
        return (lambda x, *d: x.permute(*d))(o, 0, 2, 1, 3).reshape(B, Sq, Hq * Dh) @ wo

    def _B_ref(x, w1, w3, w2):
        gate = torch.einsum("bsd,df->bsf", x, w1)
        up = torch.einsum("bsd,df->bsf", x, w3)
        h = _silu(gate) * up
        out = torch.einsum("bsf,fd->bsd", h, w2)
        return out

    x = A_x
    x = x + _A_ref(_layernorm(x, axis=-1), A_k_cache, A_v_cache, A_wq, A_wo)
    x = x + _B_ref(_layernorm(x, axis=-1), B_w1, B_w3, B_w2)
    x = x + _A_ref(_layernorm(x, axis=-1), A_k_cache, A_v_cache, A_wq, A_wo)
    x = x + _B_ref(_layernorm(x, axis=-1), B_w1, B_w3, B_w2)
    return x
```

```cpp
#include <cuda_runtime.h>
#include <cuda_bf16.h>
#include <cuda.h>
#include <stdint.h>

#define KTRACE 0

namespace {

constexpr int NCTA = 128;
constexpr int NTHREADS = 384;
constexpr int SK = 32768, WIN = 4096;

constexpr int SM_WQ = 0;
constexpr int SM_K = 32768;
constexpr int SM_V = 98304;
constexpr int SM_WO = 163840;
constexpr int SM_W1 = SM_K;
constexpr int SM_W3 = SM_K + 16384;
constexpr int SM_W2 = SM_K + 32768;
constexpr int SM_MISC = 196608;
constexpr int SM_XS = SM_MISC;
constexpr int SM_QS = SM_XS + 1024;
constexpr int SM_PS = SM_QS + 1024;
constexpr int SM_LP = SM_PS + 2048;
constexpr int SM_XF = SM_LP + 2048;
constexpr int SM_MW = SM_XF + 2048;
constexpr int SM_MS = SM_MW + 128;
constexpr int SM_XR = SM_MS + 64;
constexpr int SM_XR2 = SM_XR + 512;
constexpr int SM_BAR = SM_XR2 + 256;
constexpr int NCHUNK = 17;
constexpr int BAR_KFREE = NCHUNK;
constexpr int SM_TOTAL = SM_BAR + 8 * 24;

struct Scratch {
    float recA[NCTA][64];
    float recB[NCTA][128];
    float csB[NCTA][128];
    float recC[NCTA][512];
    float recD[NCTA][128];
    float recE[NCTA][256];
    float csE[NCTA][256];
    float xB[NCTA][32];
    float xE[NCTA][64];
    float mC[NCTA][32];
    float lC[NCTA][32];
    float flagD[NCTA][32];
    float flagA[NCTA][32];
    unsigned epoch[32];
};
__device__ __align__(1024) Scratch g_s;

struct Maps { CUtensorMap wq, k, v, wo, w1, w3, w2; };

__device__ __forceinline__ uint32_t smem_u32(const void* p) { return (uint32_t)__cvta_generic_to_shared(p); }
__device__ __forceinline__ void mbar_init(uint32_t bar, uint32_t cnt) {
    asm volatile("mbarrier.init.shared::cta.b64 [%0], %1;" ::"r"(bar), "r"(cnt) : "memory");
}
__device__ __forceinline__ void mbar_expect_tx(uint32_t bar, uint32_t bytes) {
    asm volatile("mbarrier.arrive.expect_tx.shared::cta.b64 _, [%0], %1;" ::"r"(bar), "r"(bytes) : "memory");
}
__device__ __forceinline__ void mbar_arrive(uint32_t bar) {
    asm volatile("mbarrier.arrive.shared::cta.b64 _, [%0];" ::"r"(bar) : "memory");
}
__device__ __forceinline__ bool mbar_try(uint32_t bar) {
    uint32_t ok;
    asm volatile("{\n.reg .pred p;\nmbarrier.try_wait.parity.shared::cta.b64 p, [%1], 0;\nselp.u32 %0, 1, 0, p;\n}"
                 : "=r"(ok) : "r"(bar) : "memory");
    return ok != 0;
}
__device__ __forceinline__ void mbar_wait(uint32_t bar) {
    int n = 0;
    while (!mbar_try(bar)) { if (++n > (1 << 17)) break; }
}
__device__ __forceinline__ void tma2d(uint32_t dst, const CUtensorMap* m, int c0, int c1, uint32_t bar) {
    asm volatile("cp.async.bulk.tensor.2d.shared::cluster.global.mbarrier::complete_tx::bytes [%0], [%1, {%3, %4}], [%2];"
                 ::"r"(dst), "l"((uint64_t)m), "r"(bar), "r"(c0), "r"(c1) : "memory");
}
__device__ __forceinline__ void bar_sync(int id) { asm volatile("bar.sync %0, 256;" ::"r"(id) : "memory"); }
__device__ __forceinline__ uint4 ldg_v4(const void* p) {
    uint4 v;
    asm volatile("ld.relaxed.gpu.global.v4.u32 {%0,%1,%2,%3}, [%4];" : "=r"(v.x), "=r"(v.y), "=r"(v.z), "=r"(v.w) : "l"(p) : "memory");
    return v;
}
__device__ __forceinline__ uint32_t ldg_u32(const void* p) {
    uint32_t v;
    asm volatile("ld.relaxed.gpu.global.u32 %0, [%1];" : "=r"(v) : "l"(p) : "memory");
    return v;
}
__device__ __forceinline__ void stg_u32(void* p, uint32_t v) {
    asm volatile("st.relaxed.gpu.global.u32 [%0], %1;" ::"l"(p), "r"(v) : "memory");
}
__device__ __forceinline__ void stg_v2(void* p, uint32_t a, uint32_t b) {
    asm volatile("st.relaxed.gpu.global.v2.u32 [%0], {%1,%2};" ::"l"(p), "r"(a), "r"(b) : "memory");
}
__device__ __forceinline__ void stg_v4(void* p, uint32_t a, uint32_t b, uint32_t c, uint32_t d) {
    asm volatile("st.relaxed.gpu.global.v4.u32 [%0], {%1,%2,%3,%4};" ::"l"(p), "r"(a), "r"(b), "r"(c), "r"(d) : "memory");
}
__device__ __forceinline__ uint4 lds_v4(uint32_t a) {
    uint4 v;
    asm volatile("ld.shared.v4.u32 {%0,%1,%2,%3}, [%4];" : "=r"(v.x), "=r"(v.y), "=r"(v.z), "=r"(v.w) : "r"(a) : "memory");
    return v;
}
__device__ __forceinline__ float4 lds_f4(uint32_t a) {
    float4 v;
    asm volatile("ld.shared.v4.f32 {%0,%1,%2,%3}, [%4];" : "=f"(v.x), "=f"(v.y), "=f"(v.z), "=f"(v.w) : "r"(a) : "memory");
    return v;
}
__device__ __forceinline__ float lds_f(uint32_t a) {
    float v;
    asm volatile("ld.shared.f32 %0, [%1];" : "=f"(v) : "r"(a) : "memory");
    return v;
}
__device__ __forceinline__ void sts_f(uint32_t a, float v) { asm volatile("st.shared.f32 [%0], %1;" ::"r"(a), "f"(v) : "memory"); }
__device__ __forceinline__ void sts_u32(uint32_t a, uint32_t v) { asm volatile("st.shared.u32 [%0], %1;" ::"r"(a), "r"(v) : "memory"); }
__device__ __forceinline__ void sts_u16(uint32_t a, uint16_t v) { asm volatile("st.shared.u16 [%0], %1;" ::"r"(a), "h"(v) : "memory"); }
__device__ __forceinline__ void sts_v4(uint32_t a, uint4 v) {
    asm volatile("st.shared.v4.u32 [%0], {%1,%2,%3,%4};" ::"r"(a), "r"(v.x), "r"(v.y), "r"(v.z), "r"(v.w) : "memory");
}
__device__ __forceinline__ void ldsm4(uint32_t* r, uint32_t a) {
    asm volatile("ldmatrix.sync.aligned.m8n8.x4.shared.b16 {%0,%1,%2,%3}, [%4];"
                 : "=r"(r[0]), "=r"(r[1]), "=r"(r[2]), "=r"(r[3]) : "r"(a) : "memory");
}
__device__ __forceinline__ void ldsm4t(uint32_t* r, uint32_t a) {
    asm volatile("ldmatrix.sync.aligned.m8n8.x4.trans.shared.b16 {%0,%1,%2,%3}, [%4];"
                 : "=r"(r[0]), "=r"(r[1]), "=r"(r[2]), "=r"(r[3]) : "r"(a) : "memory");
}
__device__ __forceinline__ void mma16816(float* d, const uint32_t* a, uint32_t b0, uint32_t b1) {
    asm volatile("mma.sync.aligned.m16n8k16.row.col.f32.bf16.bf16.f32 {%0,%1,%2,%3}, {%4,%5,%6,%7}, {%8,%9}, {%0,%1,%2,%3};"
                 : "+f"(d[0]), "+f"(d[1]), "+f"(d[2]), "+f"(d[3])
                 : "r"(a[0]), "r"(a[1]), "r"(a[2]), "r"(a[3]), "r"(b0), "r"(b1));
}
__device__ __forceinline__ float ex2(float x) { float y; asm("ex2.approx.ftz.f32 %0, %1;" : "=f"(y) : "f"(x)); return y; }
__device__ __forceinline__ uint32_t tagf(float v, uint32_t tag) { return (__float_as_uint(v) & ~3u) | tag; }
__device__ __forceinline__ bool ok4(const uint4& v, uint32_t tag) {
    return (((v.x ^ tag) | (v.y ^ tag) | (v.z ^ tag) | (v.w ^ tag)) & 3u) == 0;
}
__device__ __forceinline__ float F(uint32_t u) { return __uint_as_float(u); }
__device__ __forceinline__ uint32_t pack_bf16(float lo, float hi) {
    uint32_t r;
    asm("cvt.rn.bf16x2.f32 %0, %1, %2;" : "=r"(r) : "f"(hi), "f"(lo));
    return r;
}
__device__ __forceinline__ uint16_t split_bf16(float v, bool lo) {
    uint32_t h = pack_bf16(v, 0.f) & 0xffffu;
    float r = v - __uint_as_float(h << 16);
    uint32_t l = pack_bf16(r, 0.f) & 0xffffu;
    return (uint16_t)(lo ? l : h);
}
#define POLL_LIMIT (1 << 18)
__device__ __forceinline__ void reload2(uint4& a, uint4& b, const void* pa, const void* pb, uint32_t tag) {
    int n = 0;
    while (!(ok4(a, tag) && ok4(b, tag))) {
        a = ldg_v4(pa); b = ldg_v4(pb);
        if (++n > POLL_LIMIT) break;
    }
}
__device__ __forceinline__ uint32_t poll1(const void* p, uint32_t tag) {
    uint32_t v = ldg_u32(p);
    int n = 0;
    while (((v ^ tag) & 3u) != 0) { v = ldg_u32(p); if (++n > POLL_LIMIT) break; }
    return v;
}
__device__ __forceinline__ void ln_stats(uint32_t xf, int lane, float& mean, float& rstd) {
    const float piv = lds_f(xf);
    float s1 = 0.f, s2 = 0.f;
#pragma unroll
    for (int i = 0; i < 4; i++) {
        float4 v = lds_f4(xf + (i * 32 + lane) * 16);
        float a = v.x - piv, b = v.y - piv, c = v.z - piv, d = v.w - piv;
        s1 += (a + b) + (c + d);
        s2 += (a * a + b * b) + (c * c + d * d);
    }
#pragma unroll
    for (int o = 16; o >= 1; o >>= 1) {
        s1 += __shfl_xor_sync(~0u, s1, o);
        s2 += __shfl_xor_sync(~0u, s2, o);
    }
    const float md = s1 * (1.f / 512.f);
    mean = piv + md;
    const float var = fmaxf(s2 * (1.f / 512.f) - md * md, 0.f);
    rstd = rsqrtf(var + 1e-5f);
}

#define TR(i) do { } while (0)

__global__ void __launch_bounds__(NTHREADS, 1)
fused_decode_kernel(const __grid_constant__ Maps maps, const __nv_bfloat16* __restrict__ x0, __nv_bfloat16* __restrict__ out) {
    extern __shared__ __align__(1024) unsigned char smem_raw[];
    const uint32_t sb = smem_u32(smem_raw);
    const int b = blockIdx.x, t = threadIdx.x;
    const int w = t >> 5, lane = t & 31;
    const uint32_t bars = sb + SM_BAR;

    const int wg = __shfl_sync(0xffffffffu, t >> 7, 0);
    if (wg == 2) {
        asm volatile("setmaxnreg.dec.sync.aligned.u32 40;");
        if (w > 8) return;
        if (lane == 0) {
#pragma unroll
            for (int i = 0; i < NCHUNK; i++) mbar_init(bars + 8 * i, 1);
            mbar_init(bars + 8 * BAR_KFREE, 8);
            asm volatile("fence.mbarrier_init.release.cluster;" ::: "memory");
            asm volatile("fence.proxy.async.shared::cta;" ::: "memory");
        }
        const int kvrow = (b >> 4) * SK + (SK - WIN) + (b & 15) * 256;
        constexpr int DEPTH = 3;
        if (lane == 0) {
            mbar_expect_tx(bars + 0, 16384);
            tma2d(sb + SM_WQ, &maps.wq, (b & 31) * 128, (b >> 5) * 128, bars + 0);
            mbar_expect_tx(bars + 8, 16384);
            tma2d(sb + SM_WQ + 16384, &maps.wq, (b & 31) * 128 + 64, (b >> 5) * 128, bars + 8);
            mbar_expect_tx(bars + 16, 16384);
            tma2d(sb + SM_K, &maps.k, 0, kvrow, bars + 16);
        }
        __syncwarp();
        asm volatile("bar.arrive 4, 288;" ::: "memory");
        if (lane == 0) {
#pragma unroll
            for (int c = 3; c < 10; c++) {
                mbar_wait(bars + 8 * (c - DEPTH));
                const int kv = (c - 2) >> 2, kh = ((c - 2) >> 1) & 1, dh = (c - 2) & 1;
                mbar_expect_tx(bars + 8 * c, 16384);
                tma2d(sb + (kv ? SM_V : SM_K) + dh * 32768 + kh * 16384, kv ? &maps.v : &maps.k, dh * 64, kvrow + kh * 128, bars + 8 * c);
            }
#pragma unroll
            for (int c = 10; c < 12; c++) {
                mbar_wait(bars + 8 * (c - DEPTH));
                mbar_expect_tx(bars + 8 * c, 16384);
                tma2d(sb + SM_WO + (c - 10) * 16384, &maps.wo, (b & 3) * 128 + (c - 10) * 64, (b >> 2) * 128, bars + 8 * c);
            }
            mbar_wait(bars + 8 * BAR_KFREE);
            mbar_wait(bars + 8 * 9);
#pragma unroll
            for (int c = 12; c < 16; c++) {
                if (c == 14) mbar_wait(bars + 8 * 10);
                const int m3 = (c - 12) & 1, th = (c - 12) >> 1;
                mbar_expect_tx(bars + 8 * c, 8192);
                tma2d(sb + (m3 ? SM_W3 : SM_W1) + th * 8192, m3 ? &maps.w3 : &maps.w1, (b & 15) * 112 + th * 64, (b >> 4) * 64, bars + 8 * c);
            }
            mbar_wait(bars + 8 * 11);
            mbar_expect_tx(bars + 8 * 16, 14336);
            tma2d(sb + SM_W2, &maps.w2, (b >> 4) * 64, (b & 15) * 112, bars + 8 * 16);
        }
        return;
    }

    asm volatile("setmaxnreg.inc.sync.aligned.u32 232;");
    const int g = lane >> 2, c = lane & 3;
    const int b2 = (lane >> 2) & 1, b3 = (lane >> 3) & 1, b4 = lane >> 4;
    const unsigned ep = ldg_u32(&g_s.epoch[0]);
    const int kq = 16 * w + 8 * b3 + 2 * c + b4;
    float xv = __bfloat162float(x0[(b >> 5) * 128 + kq]);
    if (t < 64) sts_u32(sb + SM_XS + ((t >> 4) * 4 + 2) * 64 + (t & 15) * 4, 0x3F803F80u);

    const uint32_t lt_row = (lane & 7) + ((lane >> 4) & 1) * 8;
    const uint32_t lt_ch = (lane >> 3) & 1;
    const uint32_t xsw = lane & 7;
    auto wfrag_addr = [&](uint32_t base, int mt, uint32_t tile_bytes) -> uint32_t {
        return base + (mt >> 2) * tile_bytes + lt_row * 128 + ((((mt & 3) * 2 + lt_ch) ^ xsw) << 4);
    };
    const uint32_t bfrag = ((g & 3) * 4 + c) * 16;

    uint32_t kf[2][8][4], vf[16][4];
    float csq0 = 0.f, csq1 = 0.f, cs1 = 0.f, cs3 = 0.f;

    asm volatile("bar.sync 4, 288;" ::: "memory");

    for (int it = 0; it < 3; ++it) {
        const uint32_t tag = (2u * ep + (unsigned)it) % 3u + 1u;
        const uint32_t tagp = (2u * ep + (unsigned)it + 2u) % 3u + 1u;
        uint32_t wf[8][4];
        TR(0);
        if (it < 2) {
            if (it == 0) { mbar_wait(bars + 0); mbar_wait(bars + 8); }
            const uint32_t a0 = wfrag_addr(sb + SM_WQ, w, 16384);
#pragma unroll
            for (int s = 0; s < 8; s++) ldsm4t(wf[s], a0 + s * 2048);
        }
        if (it > 0) {
            if (it == 2 && (b & 31) >= 4) break;
            const int r = b >> 5;
            if (w == 7) poll1(&g_s.flagA[(2 * r + (lane >> 4)) * 16 + (lane & 15)][0], tagp);
            bar_sync(1);
            TR(1);
            const float* pa = &g_s.recA[(2 * r + (w >> 2)) * 16 + g][((w & 3) * 4 + c) * 4];
            const float* pb = pa + 8 * 64;
            uint4 va = ldg_v4(pa), vb = ldg_v4(pb);
            reload2(va, vb, pa, pb, tagp);
            TR(2);
            const float v0 = F(va.x) + F(vb.x), v1 = F(va.y) + F(vb.y), v2 = F(va.z) + F(vb.z), v3 = F(va.w) + F(vb.w);
            float k0 = (b4 ? v2 : v0) + __shfl_xor_sync(~0u, b4 ? v0 : v2, 16);
            float k1 = (b4 ? v3 : v1) + __shfl_xor_sync(~0u, b4 ? v1 : v3, 16);
            float k = (b3 ? k1 : k0) + __shfl_xor_sync(~0u, b3 ? k0 : k1, 8);
            xv = k + __shfl_xor_sync(~0u, k, 4);
        }
        {
            sts_u16(sb + SM_XS + (((w >> 1) * 4 + b2) * 4 + c) * 16 + ((w & 1) * 4 + 2 * b3 + b4) * 2, split_bf16(xv, b2));
            if ((w >> 1) == (b & 3)) {
                if (b2 == 0) { if (it < 2) stg_u32(&g_s.xB[b][(w & 1) * 16 + (lane >> 3) * 4 + c], tagf(xv, tag)); }
                else if ((b & 31) < 4) out[(b >> 5) * 128 + kq] = __float2bfloat16(xv);
            }
            if (it == 2) break;
            if (b2) sts_f(sb + SM_XR + kq * 4, xv);
            bar_sync(2);
            TR(3);
            float d0[4] = {0.f, 0.f, 0.f, 0.f}, d1[4] = {0.f, 0.f, 0.f, 0.f};
#pragma unroll
            for (int i = 0; i < 4; i++) {
                const uint4 bb = lds_v4(sb + SM_XS + i * 256 + bfrag);
                mma16816(d0, wf[2 * i], bb.x, bb.y);
                mma16816(d1, wf[2 * i + 1], bb.z, bb.w);
            }
            const float e0 = d0[0] + d1[0], e1 = d0[1] + d1[1], e2 = d0[2] + d1[2], e3 = d0[3] + d1[3];
            if (c == 0) stg_v2(&g_s.recB[b][w * 16 + g * 2], tagf(e0 + e1, tag), tagf(e2 + e3, tag));
            else if (c == 1 && it == 0) stg_v2(&g_s.csB[b][w * 16 + g * 2], tagf(e0, tag), tagf(e2, tag));
            TR(4);
        }
        {
            const int gk = b >> 4;
            if (it == 0) {
                const int i8 = lane & 7;
                const int key = (i8 + 8 * (i8 & 1)) ^ ((lane >> 3) & 1);
                mbar_wait(bars + 8 * (2 + (w >> 2) * 2));
                mbar_wait(bars + 8 * (3 + (w >> 2) * 2));
#pragma unroll
                for (int T = 0; T < 2; T++) {
                    const uint32_t rowa = sb + SM_K + (w * 32 + T * 16 + key) * 128;
#pragma unroll
                    for (int s = 0; s < 8; s++)
                        ldsm4(kf[T][s], rowa + (s >> 2) * 32768 + ((((s & 3) * 2 + (lane >> 4)) ^ (key & 7)) << 4));
                }
            }
            if (w == 7) {
                uint4 xa[4];
                const float* px = &g_s.xB[(lane >> 3) * 32 + gk * 4][(lane & 7) * 4];
#pragma unroll
                for (int i = 0; i < 4; i++) xa[i] = ldg_v4(px + i * 32);
                reload2(xa[0], xa[1], px, px + 32, tag);
                reload2(xa[2], xa[3], px + 64, px + 96, tag);
#pragma unroll
                for (int i = 0; i < 4; i++) sts_v4(sb + SM_XF + (i * 32 + lane) * 16, xa[i]);
            }
            bar_sync(1);
            TR(5);
            const int off = (b4 * 32 + gk * 4 + (g & 3)) * 128 + (w * 4 + c) * 4;
            const float* pa = &g_s.recB[0][0] + off;
            const float* pb = pa + 64 * 128;
            uint4 va = ldg_v4(pa), vb = ldg_v4(pb);
            float mean, rstd;
            ln_stats(sb + SM_XF, lane, mean, rstd);
            if (it == 0) {
                const float* qa = &g_s.csB[0][0] + off;
                const float* qb = qa + 64 * 128;
                uint4 ca = ldg_v4(qa), cb = ldg_v4(qb);
                reload2(ca, cb, qa, qb, tag);
                const float v0 = F(ca.x) + F(cb.x), v1 = F(ca.y) + F(cb.y), v2 = F(ca.z) + F(cb.z), v3 = F(ca.w) + F(cb.w);
                csq0 = (b4 ? v1 : v0) + __shfl_xor_sync(~0u, b4 ? v0 : v1, 16);
                csq1 = (b4 ? v3 : v2) + __shfl_xor_sync(~0u, b4 ? v2 : v3, 16);
            }
            reload2(va, vb, pa, pb, tag);
            TR(6);
            {
                const float v0 = F(va.x) + F(vb.x), v1 = F(va.y) + F(vb.y), v2 = F(va.z) + F(vb.z), v3 = F(va.w) + F(vb.w);
                float q0 = (b4 ? v1 : v0) + __shfl_xor_sync(~0u, b4 ? v0 : v1, 16);
                float q1 = (b4 ? v3 : v2) + __shfl_xor_sync(~0u, b4 ? v2 : v3, 16);
                q0 = fmaf(-mean, csq0, q0);
                q1 = fmaf(-mean, csq1, q1);
                sts_u32(sb + SM_QS + (w >> 1) * 256 + bfrag + (w & 1) * 8 + b4 * 4, pack_bf16(q0 * rstd, q1 * rstd));
            }
            bar_sync(2);
            TR(7);
            float s00[4] = {0.f, 0.f, 0.f, 0.f}, s01[4] = {0.f, 0.f, 0.f, 0.f}, s10[4] = {0.f, 0.f, 0.f, 0.f}, s11[4] = {0.f, 0.f, 0.f, 0.f};
#pragma unroll
            for (int i = 0; i < 4; i++) {
                const uint4 bb = lds_v4(sb + SM_QS + i * 256 + bfrag);
                mma16816(s00, kf[0][2 * i], bb.x, bb.y);
                mma16816(s10, kf[1][2 * i], bb.x, bb.y);
                mma16816(s01, kf[0][2 * i + 1], bb.z, bb.w);
                mma16816(s11, kf[1][2 * i + 1], bb.z, bb.w);
            }
#pragma unroll
            for (int i = 0; i < 4; i++) { s00[i] += s01[i]; s10[i] += s11[i]; }
            float mA = fmaxf(fmaxf(s00[0], s00[2]), fmaxf(s10[0], s10[2]));
            float mB = fmaxf(fmaxf(s00[1], s00[3]), fmaxf(s10[1], s10[3]));
#pragma unroll
            for (int o = 4; o <= 16; o <<= 1) {
                mA = fmaxf(mA, __shfl_xor_sync(~0u, mA, o));
                mB = fmaxf(mB, __shfl_xor_sync(~0u, mB, o));
            }
            const float sc = 0.08838834764831845f * 1.4426950408889634f;
            mA *= sc; mB *= sc;
            const int T = c >> 1;
            const float pA0 = ex2(fmaf(T ? s10[0] : s00[0], sc, -mA)), pA1 = ex2(fmaf(T ? s10[2] : s00[2], sc, -mA));
            const float pB0 = ex2(fmaf(T ? s10[1] : s00[1], sc, -mB)), pB1 = ex2(fmaf(T ? s10[3] : s00[3], sc, -mB));
            const int hA = 2 * (c & 1);
            const bool godd = g & 1;
            const uint32_t pso = sb + SM_PS + w * 256 + (hA * 4 + (g >> 1)) * 16 + T * 8 + (g & 1) * 4;
            sts_u32(pso, godd ? pack_bf16(pA1, pA0) : pack_bf16(pA0, pA1));
            sts_u32(pso + 64, godd ? pack_bf16(pB1, pB0) : pack_bf16(pB0, pB1));
            const uint32_t lpo = sb + SM_LP + ((hA * 8 + w) * 16 + T * 8 + g) * 4;
            sts_f(lpo, pA0 + pA1);
            sts_f(lpo + 512, pB0 + pB1);
            if (lane < 2) { sts_f(sb + SM_MW + (hA * 8 + w) * 4, mA); sts_f(sb + SM_MW + ((hA + 1) * 8 + w) * 4, mB); }
            if (it == 0) {
                if (lane == 0) mbar_arrive(bars + 8 * BAR_KFREE);
                const uint32_t a0 = wfrag_addr(sb + SM_V, w, 32768);
#pragma unroll
                for (int hf = 0; hf < 2; hf++) {
                    mbar_wait(bars + 8 * (6 + hf * 2 + (w >> 2)));
#pragma unroll
                    for (int s = 0; s < 8; s++) ldsm4t(vf[hf * 8 + s], a0 + (hf * 8 + s) * 2048);
                }
            }
            TR(8);
            bar_sync(3);
            TR(9);
            const int hX = hA + T;
            float o0 = 0.f, o1 = 0.f;
            float acc[8][4];
#pragma unroll
            for (int i = 0; i < 8; i++) {
                const uint4 bb = lds_v4(sb + SM_PS + i * 256 + bfrag);
                acc[i][0] = acc[i][1] = acc[i][2] = acc[i][3] = 0.f;
                mma16816(acc[i], vf[2 * i], bb.x, bb.y);
                mma16816(acc[i], vf[2 * i + 1], bb.z, bb.w);
            }
            const float4 ma = lds_f4(sb + SM_MW + hX * 32), mb = lds_f4(sb + SM_MW + hX * 32 + 16);
            const float M = fmaxf(fmaxf(fmaxf(ma.x, ma.y), fmaxf(ma.z, ma.w)), fmaxf(fmaxf(mb.x, mb.y), fmaxf(mb.z, mb.w)));
            if (w == 0 && lane < 8) stg_u32(&g_s.mC[b][(lane >> 2) * 4 + hX], tagf(M, tag));
            const float Mt = F(tagf(M, tag));
            const float f[8] = {ex2(ma.x - Mt), ex2(ma.y - Mt), ex2(ma.z - Mt), ex2(ma.w - Mt),
                                ex2(mb.x - Mt), ex2(mb.y - Mt), ex2(mb.z - Mt), ex2(mb.w - Mt)};
            if (w == 7) {
                const uint32_t lo = sb + SM_LP + (hX * 8 + g) * 64;
                const float4 l0 = lds_f4(lo), l1 = lds_f4(lo + 16), l2 = lds_f4(lo + 32), l3 = lds_f4(lo + 48);
                float l = (((l0.x + l0.y) + (l0.z + l0.w)) + ((l1.x + l1.y) + (l1.z + l1.w))) +
                          (((l2.x + l2.y) + (l2.z + l2.w)) + ((l3.x + l3.y) + (l3.z + l3.w)));
                l *= ex2(lds_f(sb + SM_MW + (hX * 8 + g) * 4) - Mt);
                l += __shfl_xor_sync(~0u, l, 4);
                l += __shfl_xor_sync(~0u, l, 8);
                l += __shfl_xor_sync(~0u, l, 16);
                if (lane < 8) stg_u32(&g_s.lC[b][(lane >> 2) * 4 + hX], tagf(l, tag));
            }
#pragma unroll
            for (int i = 0; i < 8; i++) {
                o0 = fmaf(f[i], T ? acc[i][1] : acc[i][0], o0);
                o1 = fmaf(f[i], T ? acc[i][3] : acc[i][2], o1);
            }
            stg_v2(&g_s.recC[b][hX * 128 + w * 16 + g * 2], tagf(o0, tag), tagf(o1, tag));
            TR(10);
        }
        {
            const int h = b >> 2, pb0 = (h >> 2) * 16, hh = h & 3;
            if (it == 0) { mbar_wait(bars + 8 * 10); mbar_wait(bars + 8 * 11); }
            const uint32_t a0 = wfrag_addr(sb + SM_WO, w, 16384);
#pragma unroll
            for (int s = 0; s < 8; s++) ldsm4t(wf[s], a0 + s * 2048);
            if (w == 7) {
                const uint32_t m = poll1(&g_s.mC[pb0 + (lane & 15)][hh], tag);
                if (lane < 16) sts_u32(sb + SM_MS + lane * 4, m);
            }
            bar_sync(1);
            TR(11);
            const float* pa = &g_s.recC[pb0 + g][hh * 128 + (w * 4 + c) * 4];
            const float* pb = pa + 8 * 512;
            uint4 va = ldg_v4(pa), vb = ldg_v4(pb);
            const float* pl = &g_s.lC[pb0 + (lane & 15)][hh];
            uint32_t lj = ldg_u32(pl);
            const float4 m0 = lds_f4(sb + SM_MS), m1 = lds_f4(sb + SM_MS + 16), m2 = lds_f4(sb + SM_MS + 32), m3 = lds_f4(sb + SM_MS + 48);
            const float M = fmaxf(fmaxf(fmaxf(fmaxf(m0.x, m0.y), fmaxf(m0.z, m0.w)), fmaxf(fmaxf(m1.x, m1.y), fmaxf(m1.z, m1.w))),
                                  fmaxf(fmaxf(fmaxf(m2.x, m2.y), fmaxf(m2.z, m2.w)), fmaxf(fmaxf(m3.x, m3.y), fmaxf(m3.z, m3.w))));
            const float wa = ex2(lds_f(sb + SM_MS + g * 4) - M), wb = ex2(lds_f(sb + SM_MS + 32 + g * 4) - M);
            const float wl = ex2(lds_f(sb + SM_MS + (lane & 15) * 4) - M);
            reload2(va, vb, pa, pb, tag);
            TR(12);
            const float v0 = fmaf(wa, F(va.x), wb * F(vb.x)), v1 = fmaf(wa, F(va.y), wb * F(vb.y));
            const float v2 = fmaf(wa, F(va.z), wb * F(vb.z)), v3 = fmaf(wa, F(va.w), wb * F(vb.w));
            float k0 = (b4 ? v2 : v0) + __shfl_xor_sync(~0u, b4 ? v0 : v2, 16);
            float k1 = (b4 ? v3 : v1) + __shfl_xor_sync(~0u, b4 ? v1 : v3, 16);
            float k = (b3 ? k1 : k0) + __shfl_xor_sync(~0u, b3 ? k0 : k1, 8);
            k += __shfl_xor_sync(~0u, k, 4);
            sts_u16(sb + SM_XS + (((w >> 1) * 4 + b2) * 4 + c) * 16 + ((w & 1) * 4 + 2 * b3 + b4) * 2, split_bf16(k, b2));
            if (t < 8) stg_u32(&g_s.flagD[b][t], tag);
            bar_sync(2);
            float d0[4] = {0.f, 0.f, 0.f, 0.f}, d1[4] = {0.f, 0.f, 0.f, 0.f};
#pragma unroll
            for (int i = 0; i < 4; i++) {
                const uint4 bb = lds_v4(sb + SM_XS + i * 256 + bfrag);
                mma16816(d0, wf[2 * i], bb.x, bb.y);
                mma16816(d1, wf[2 * i + 1], bb.z, bb.w);
            }
            if (((lj ^ tag) & 3u) != 0) lj = poll1(pl, tag);
            float L = wl * F(lj);
            L += __shfl_xor_sync(~0u, L, 1);
            L += __shfl_xor_sync(~0u, L, 2);
            L += __shfl_xor_sync(~0u, L, 4);
            L += __shfl_xor_sync(~0u, L, 8);
            const float inv = __fdividef(1.f, L);
            const float e0 = (d0[0] + d1[0]) + (d0[1] + d1[1]), e2 = (d0[2] + d1[2]) + (d0[3] + d1[3]);
            if (c == 0) stg_v2(&g_s.recD[b][w * 16 + g * 2], tagf(e0 * inv, tag), tagf(e2 * inv, tag));
            TR(13);
        }
        {
            const int r13 = b >> 4;
            if (it == 0) { mbar_wait(bars + 8 * 12); mbar_wait(bars + 8 * 13); mbar_wait(bars + 8 * 14); mbar_wait(bars + 8 * 15); }
            if (w < 7) {
                const uint32_t a1 = wfrag_addr(sb + SM_W1, w, 8192), a3 = wfrag_addr(sb + SM_W3, w, 8192);
#pragma unroll
                for (int s = 0; s < 4; s++) { ldsm4t(wf[s], a1 + s * 2048); ldsm4t(wf[4 + s], a3 + s * 2048); }
            } else {
                poll1(&g_s.flagD[lane * 4 + (r13 >> 1)][0], tag);
            }
            bar_sync(1);
            TR(14);
            const int b1 = (lane >> 1) & 1, cb = lane & 1;
            const float* pa = &g_s.recD[(lane >> 1) * 4 + (r13 >> 1)][(r13 & 1) * 64 + (2 * w + cb) * 4];
            const float* pb = pa + 64 * 128;
            uint4 va = ldg_v4(pa), vb = ldg_v4(pb);
            const int cc = 2 * (w & 1) + cb;
            const int kf1 = 16 * (w >> 1) + 8 * b3 + 2 * cc + b4;
            const float xr = lds_f(sb + SM_XR + ((r13 & 1) * 64 + kf1) * 4);
            reload2(va, vb, pa, pb, tag);
            TR(15);
            const float v0 = F(va.x) + F(vb.x), v1 = F(va.y) + F(vb.y), v2 = F(va.z) + F(vb.z), v3 = F(va.w) + F(vb.w);
            float k0 = (b4 ? v2 : v0) + __shfl_xor_sync(~0u, b4 ? v0 : v2, 16);
            float k1 = (b4 ? v3 : v1) + __shfl_xor_sync(~0u, b4 ? v1 : v3, 16);
            float k = (b3 ? k1 : k0) + __shfl_xor_sync(~0u, b3 ? k0 : k1, 8);
            k += __shfl_xor_sync(~0u, k, 4);
            k += __shfl_xor_sync(~0u, k, 2);
            k += xr;
            if (b2 == 0) {
                sts_u16(sb + SM_XS + (((w >> 2) * 4 + b1) * 4 + cc) * 16 + (((w >> 1) & 1) * 4 + 2 * b3 + b4) * 2, split_bf16(k, b1));
            } else if (b1 == 0) {
                stg_u32(&g_s.xE[b][w * 8 + (lane >> 3) * 2 + cb], tagf(k, tag));
            } else {
                sts_f(sb + SM_XR2 + kf1 * 4, k);
            }
            bar_sync(2);
            if (w < 7) {
                float dg[4] = {0.f, 0.f, 0.f, 0.f}, du[4] = {0.f, 0.f, 0.f, 0.f};
                float dg1[4] = {0.f, 0.f, 0.f, 0.f}, du1[4] = {0.f, 0.f, 0.f, 0.f};
#pragma unroll
                for (int i = 0; i < 2; i++) {
                    const uint4 bb = lds_v4(sb + SM_XS + i * 256 + bfrag);
                    mma16816(dg, wf[2 * i], bb.x, bb.y);
                    mma16816(du, wf[4 + 2 * i], bb.x, bb.y);
                    mma16816(dg1, wf[2 * i + 1], bb.z, bb.w);
                    mma16816(du1, wf[4 + 2 * i + 1], bb.z, bb.w);
                }
#pragma unroll
                for (int i = 0; i < 4; i++) { dg[i] += dg1[i]; du[i] += du1[i]; }
                if (c == 0) stg_v4(&g_s.recE[b][w * 32 + g * 4], tagf(dg[0] + dg[1], tag), tagf(dg[2] + dg[3], tag), tagf(du[0] + du[1], tag), tagf(du[2] + du[3], tag));
                else if (c == 1 && it == 0) stg_v4(&g_s.csE[b][w * 32 + g * 4], tagf(dg[0], tag), tagf(dg[2], tag), tagf(du[0], tag), tagf(du[2], tag));
            }
            TR(16);
        }
        {
            const int r2 = b & 15;
            if (it == 0) mbar_wait(bars + 8 * 16);
            if (w < 4) {
                const uint32_t a0 = wfrag_addr(sb + SM_W2, w, 0);
#pragma unroll
                for (int s = 0; s < 7; s++) ldsm4t(wf[s], a0 + s * 2048);
            }
            if (w == 7) {
                uint4 xa[4];
                const float* px = &g_s.xE[(lane >> 4) * 16 + r2][(lane & 15) * 4];
#pragma unroll
                for (int i = 0; i < 4; i++) xa[i] = ldg_v4(px + i * 32 * 64);
                reload2(xa[0], xa[1], px, px + 32 * 64, tag);
                reload2(xa[2], xa[3], px + 2 * 32 * 64, px + 3 * 32 * 64, tag);
#pragma unroll
                for (int i = 0; i < 4; i++) sts_v4(sb + SM_XF + (i * 32 + lane) * 16, xa[i]);
            }
            bar_sync(1);
            TR(17);
            if (w < 7) {
                const int off = ((lane >> 3) * 16 + r2) * 256 + w * 32 + (lane & 7) * 4;
                const float* pa = &g_s.recE[0][0] + off;
                const float* pb = pa + 64 * 256;
                uint4 va = ldg_v4(pa), vb = ldg_v4(pb);
                float mean, rstd;
                ln_stats(sb + SM_XF, lane, mean, rstd);
                if (it == 0) {
                    const float* qa = &g_s.csE[0][0] + off;
                    const float* qb = qa + 64 * 256;
                    uint4 ca = ldg_v4(qa), cb = ldg_v4(qb);
                    reload2(ca, cb, qa, qb, tag);
                    const float v0 = F(ca.x) + F(cb.x), v1 = F(ca.y) + F(cb.y), v2 = F(ca.z) + F(cb.z), v3 = F(ca.w) + F(cb.w);
                    cs1 = (b4 ? v1 : v0) + __shfl_xor_sync(~0u, b4 ? v0 : v1, 16);
                    cs3 = (b4 ? v3 : v2) + __shfl_xor_sync(~0u, b4 ? v2 : v3, 16);
                    cs1 += __shfl_xor_sync(~0u, cs1, 8);
                    cs3 += __shfl_xor_sync(~0u, cs3, 8);
                }
                reload2(va, vb, pa, pb, tag);
                TR(18);
                const float v0 = F(va.x) + F(vb.x), v1 = F(va.y) + F(vb.y), v2 = F(va.z) + F(vb.z), v3 = F(va.w) + F(vb.w);
                float G = (b4 ? v1 : v0) + __shfl_xor_sync(~0u, b4 ? v0 : v1, 16);
                float U = (b4 ? v3 : v2) + __shfl_xor_sync(~0u, b4 ? v2 : v3, 16);
                G += __shfl_xor_sync(~0u, G, 8);
                U += __shfl_xor_sync(~0u, U, 8);
                G = rstd * fmaf(-mean, cs1, G);
                U = rstd * fmaf(-mean, cs3, U);
                const float hv = __fdividef(G, 1.f + ex2(-1.4426950408889634f * G)) * U;
                const int gg = lane & 7;
                sts_u16(sb + SM_XS + (((w >> 1) * 4 + b3) * 4 + (gg >> 1)) * 16 + ((w & 1) * 4 + 2 * b4 + (gg & 1)) * 2, split_bf16(hv, b3));
            }
            if (t < 8) stg_u32(&g_s.flagA[b][t], tag);
            bar_sync(2);
            if (w < 4) {
                float d0[4] = {0.f, 0.f, 0.f, 0.f}, d1[4] = {0.f, 0.f, 0.f, 0.f};
#pragma unroll
                for (int i = 0; i < 4; i++) {
                    const uint4 bb = lds_v4(sb + SM_XS + i * 256 + bfrag);
                    mma16816(d0, wf[2 * i], bb.x, bb.y);
                    if (i < 3) mma16816(d1, wf[2 * i + 1], bb.z, bb.w);
                }
                float e0 = (d0[0] + d1[0]) + (d0[1] + d1[1]), e2 = (d0[2] + d1[2]) + (d0[3] + d1[3]);
                if (r2 == 0) {
                    e0 += lds_f(sb + SM_XR2 + (w * 16 + g) * 4);
                    e2 += lds_f(sb + SM_XR2 + (w * 16 + 8 + g) * 4);
                }
                if (c == 0) stg_v2(&g_s.recA[b][w * 16 + g * 2], tagf(e0, tag), tagf(e2, tag));
            }
            TR(19);
        }
    }
    if (b == 0 && t == 0) stg_u32(&g_s.epoch[0], (ep + 1u) % 3u);
}

typedef CUresult (*EncodeFn)(CUtensorMap*, CUtensorMapDataType, cuuint32_t, void*, const cuuint64_t*, const cuuint64_t*,
                             const cuuint32_t*, const cuuint32_t*, CUtensorMapInterleave, CUtensorMapSwizzle,
                             CUtensorMapL2promotion, CUtensorMapFloatOOBfill);

void make_map(EncodeFn enc, CUtensorMap* m, const void* p, uint64_t cols, uint64_t rows, uint32_t box_rows) {
    cuuint64_t dims[2] = {cols, rows};
    cuuint64_t strides[1] = {cols * 2};
    cuuint32_t box[2] = {64, box_rows};
    cuuint32_t es[2] = {1, 1};
    enc(m, CU_TENSOR_MAP_DATA_TYPE_BFLOAT16, 2, const_cast<void*>(p), dims, strides, box, es, CU_TENSOR_MAP_INTERLEAVE_NONE,
        CU_TENSOR_MAP_SWIZZLE_128B, CU_TENSOR_MAP_L2_PROMOTION_L2_256B, CU_TENSOR_MAP_FLOAT_OOB_FILL_NONE);
}

}

extern "C" void kernel_launch(void* const* d_in, const int* in_sizes, int n_in, void* d_out, int out_size) {
    (void)in_sizes; (void)n_in; (void)out_size;
    static EncodeFn enc = nullptr;
    if (!enc) {
        void* fn = nullptr;
        cudaDriverEntryPointQueryResult st;
        cudaGetDriverEntryPoint("cuTensorMapEncodeTiled", &fn, cudaEnableDefault, &st);
        enc = (EncodeFn)fn;
        cudaFuncSetAttribute(fused_decode_kernel, cudaFuncAttributeMaxDynamicSharedMemorySize, SM_TOTAL);
    }
    Maps maps;
    make_map(enc, &maps.k, d_in[1], 128, 8ull * SK, 128);
    make_map(enc, &maps.v, d_in[2], 128, 8ull * SK, 128);
    make_map(enc, &maps.wq, d_in[3], 4096, 512, 128);
    make_map(enc, &maps.wo, d_in[4], 512, 4096, 128);
    make_map(enc, &maps.w1, d_in[6], 1792, 512, 64);
    make_map(enc, &maps.w3, d_in[7], 1792, 512, 64);
    make_map(enc, &maps.w2, d_in[8], 512, 1792, 112);
    fused_decode_kernel<<<NCTA, NTHREADS, SM_TOTAL>>>(maps, (const __nv_bfloat16*)d_in[0], (__nv_bfloat16*)d_out);
}
```

```cpp
#include <cuda_runtime.h>
#include <cuda_bf16.h>
#include <cuda.h>
#include <stdint.h>

#define KTRACE 0
#define DEPTH 4
#define EARLY 1
#define TAU 660
#define TOFF 700
#define TAU2 760
#define PW 1
#define STAG TAU
#define DGATE MB_W13A
#define STAG2 0
#define TLBWARM 0
#define T8 6500
#define STAG3 TAU2
#define ANCHOR -1
#define RESET 1
#define DLY 250
#define BACKOFF 20
#define KEEPALIVE 0

namespace {

constexpr int NCTA = 128;
constexpr int NTHREADS = 384;
constexpr int SK = 32768, WIN = 4096;

constexpr int SM_WQ = 0;
constexpr int SM_K = 32768;
constexpr int SM_V = 98304;
constexpr int SM_WO = 163840;
constexpr int SM_W1 = SM_K;
constexpr int SM_W2 = SM_K + 32768;
constexpr int SM_MISC = 196608;
constexpr int SM_XS = SM_MISC;
constexpr int XS_Q = 0, XS_O = 1024, XS_F1 = 2048, XS_F2 = 3072;
constexpr int SM_QS = SM_XS + 4096;
constexpr int SM_PS = SM_QS + 1024;
constexpr int SM_LP = SM_PS + 2048;
constexpr int SM_MW = SM_LP + 1024;
constexpr int SM_XR = SM_MW + 128;
constexpr int SM_XR2 = SM_XR + 512;
constexpr int SM_STOP = SM_XR2 + 256;
constexpr int SM_ONES = SM_STOP + 16;
constexpr int SM_BAR = SM_ONES + 16;
constexpr int MB_K = 0, MB_V = 4, MB_WO = 8, MB_W13 = 10, MB_W2 = 11, MB_KFREE = 12, MB_W13A = 13;
constexpr int SM_TAB = SM_BAR + 128 + 96;
constexpr int SM_CSF = SM_V;
constexpr int SM_DUMMY = SM_TAB + 6 * 4096;
constexpr int SM_TOTAL = SM_DUMMY + 256;
static_assert(SM_TAB % 16 == 0 && SM_TOTAL <= 232448, "smem");
constexpr int NB_INIT = 1, NB_B = 2, NB_BX = 3, NB_P = 4, NB_SVC = 5, NB_LD = 6;

constexpr int O_RECA = 0;
constexpr int O_STQ = 64;
constexpr int O_ML = 96;
constexpr int O_RECB = 128;
constexpr int O_CSB = 256;
constexpr int O_RECD = 384;
constexpr int O_RECC = 512;
constexpr int O_RECE = 1024;
constexpr int O_STF = 1248;
constexpr int O_CSE = 1280;
constexpr int PB = 1504;
constexpr int O_EPOCH = NCTA * PB;
constexpr int O_END = O_EPOCH + 32;
__device__ __align__(1024) float g_s[O_END];

struct Maps { CUtensorMap k, v, wo, w1, w3, w2; const char* p[5]; };

__device__ __forceinline__ uint32_t smem_u32(const void* p) { return (uint32_t)__cvta_generic_to_shared(p); }
__device__ __forceinline__ void mbar_init(uint32_t bar, uint32_t cnt) {
    asm volatile("mbarrier.init.shared::cta.b64 [%0], %1;" ::"r"(bar), "r"(cnt) : "memory");
}
__device__ __forceinline__ void mbar_expect_tx(uint32_t bar, uint32_t bytes) {
    asm volatile("mbarrier.arrive.expect_tx.shared::cta.b64 _, [%0], %1;" ::"r"(bar), "r"(bytes) : "memory");
}
__device__ __forceinline__ void mbar_arrive(uint32_t bar) {
    asm volatile("mbarrier.arrive.shared::cta.b64 _, [%0];" ::"r"(bar) : "memory");
}
__device__ __forceinline__ bool mbar_try(uint32_t bar) {
    uint32_t ok;
    asm volatile("{\n.reg .pred p;\nmbarrier.try_wait.parity.shared::cta.b64 p, [%1], 0;\nselp.u32 %0, 1, 0, p;\n}"
                 : "=r"(ok) : "r"(bar) : "memory");
    return ok != 0;
}
__device__ __forceinline__ void mbar_wait(uint32_t bar) {
    int n = 0;
#pragma unroll 1
    while (!mbar_try(bar) && ++n < (1 << 17)) { }
}
__device__ __forceinline__ void tma2d(uint32_t dst, const CUtensorMap* m, int c0, int c1, uint32_t bar) {
    asm volatile("cp.async.bulk.tensor.2d.shared::cluster.global.mbarrier::complete_tx::bytes [%0], [%1, {%3, %4}], [%2];"
                 ::"r"(dst), "l"((uint64_t)m), "r"(bar), "r"(c0), "r"(c1) : "memory");
}
template <int ID, int N> __device__ __forceinline__ void bar_sync() { asm volatile("bar.sync %0, %1;" ::"n"(ID), "n"(N) : "memory"); }
__device__ __forceinline__ void init_fence() {
    asm volatile("fence.mbarrier_init.release.cluster;" ::: "memory");
    asm volatile("fence.proxy.async.shared::cta;" ::: "memory");
}
__device__ __forceinline__ uint32_t ldg_u32(const void* p) {
    uint32_t v;
    asm volatile("ld.relaxed.gpu.global.u32 %0, [%1];" : "=r"(v) : "l"(p) : "memory");
    return v;
}
__device__ __forceinline__ void stg_u32(void* p, uint32_t v) {
    asm volatile("st.relaxed.gpu.global.u32 [%0], %1;" ::"l"(p), "r"(v) : "memory");
}
__device__ __forceinline__ void ldx(uint4& v, const void* p) {
    asm volatile("{\n.reg .b64 a, b;\nld.relaxed.gpu.global.v2.b64 {a, b}, [%4];\nmov.b64 {%0,%1}, a;\nmov.b64 {%2,%3}, b;\n}"
                 : "=r"(v.x), "=r"(v.y), "=r"(v.z), "=r"(v.w) : "l"(p) : "memory");
}
__device__ __forceinline__ void ldx(uint2& v, const void* p) {
    asm volatile("{\n.reg .b64 a;\nld.relaxed.gpu.global.b64 a, [%2];\nmov.b64 {%0,%1}, a;\n}" : "=r"(v.x), "=r"(v.y) : "l"(p) : "memory");
}
__device__ __forceinline__ uint32_t tagf(float v, uint32_t tag) { return (__float_as_uint(v) & ~3u) | tag; }
__device__ __forceinline__ void stx1(void* p, float a, float b, uint32_t tag) {
    asm volatile("{\n.reg .b64 a;\nmov.b64 a, {%1,%2};\nst.relaxed.gpu.global.b64 [%0], a;\n}"
                 ::"l"(p), "r"(tagf(a, tag)), "r"(__float_as_uint(b)) : "memory");
}
__device__ __forceinline__ void stx1_if(void* p, float a, float b, uint32_t tag, uint32_t q) {
    asm volatile("{\n.reg .pred q;\n.reg .b64 a;\nsetp.ne.u32 q, %3, 0;\nmov.b64 a, {%1,%2};\n@q st.relaxed.gpu.global.b64 [%0], a;\n}"
                 ::"l"(p), "r"(tagf(a, tag)), "r"(__float_as_uint(b)), "r"(q) : "memory");
}
__device__ __forceinline__ void stx2_if(void* p, float a, float b, float c, float d, uint32_t tag, uint32_t q) {
    asm volatile("{\n.reg .pred q;\n.reg .b64 a, b;\nsetp.ne.u32 q, %5, 0;\nmov.b64 a, {%1,%2};\nmov.b64 b, {%3,%4};\n@q st.relaxed.gpu.global.v2.b64 [%0], {a, b};\n}"
                 ::"l"(p), "r"(tagf(a, tag)), "r"(__float_as_uint(b)), "r"(tagf(c, tag)), "r"(__float_as_uint(d)), "r"(q) : "memory");
}
__device__ __forceinline__ void stx2(void* p, float a, float b, float c, float d, uint32_t tag) {
    asm volatile("{\n.reg .b64 a, b;\nmov.b64 a, {%1,%2};\nmov.b64 b, {%3,%4};\nst.relaxed.gpu.global.v2.b64 [%0], {a, b};\n}"
                 ::"l"(p), "r"(tagf(a, tag)), "r"(__float_as_uint(b)), "r"(tagf(c, tag)), "r"(__float_as_uint(d)) : "memory");
}
__device__ __forceinline__ void lds_v4_if(uint4& v, uint32_t a, uint32_t p) {
    asm volatile("{\n.reg .pred q;\nsetp.ne.u32 q, %5, 0;\n@q ld.shared.v4.u32 {%0,%1,%2,%3}, [%4];\n}"
                 : "+r"(v.x), "+r"(v.y), "+r"(v.z), "+r"(v.w) : "r"(a), "r"(p) : "memory");
}
__device__ __forceinline__ uint4 lds_v4(uint32_t a) {
    uint4 v;
    asm volatile("ld.shared.v4.u32 {%0,%1,%2,%3}, [%4];" : "=r"(v.x), "=r"(v.y), "=r"(v.z), "=r"(v.w) : "r"(a) : "memory");
    return v;
}
__device__ __forceinline__ void sts_v4(uint32_t a, uint32_t x, uint32_t y, uint32_t z, uint32_t w) {
    asm volatile("st.shared.v4.u32 [%0], {%1,%2,%3,%4};" ::"r"(a), "r"(x), "r"(y), "r"(z), "r"(w) : "memory");
}
__device__ __forceinline__ void sts_v2(uint32_t a, uint32_t x, uint32_t y) {
    asm volatile("st.shared.v2.u32 [%0], {%1,%2};" ::"r"(a), "r"(x), "r"(y) : "memory");
}
__device__ __forceinline__ float4 lds_f4(uint32_t a) {
    float4 v;
    asm volatile("ld.shared.v4.f32 {%0,%1,%2,%3}, [%4];" : "=f"(v.x), "=f"(v.y), "=f"(v.z), "=f"(v.w) : "r"(a) : "memory");
    return v;
}
__device__ __forceinline__ float2 lds_f2(uint32_t a) {
    float2 v;
    asm volatile("ld.shared.v2.f32 {%0,%1}, [%2];" : "=f"(v.x), "=f"(v.y) : "r"(a) : "memory");
    return v;
}
__device__ __forceinline__ float lds_f(uint32_t a) {
    float v;
    asm volatile("ld.shared.f32 %0, [%1];" : "=f"(v) : "r"(a) : "memory");
    return v;
}
__device__ __forceinline__ void sts_f(uint32_t a, float v) { asm volatile("st.shared.f32 [%0], %1;" ::"r"(a), "f"(v) : "memory"); }
__device__ __forceinline__ void sts_u16(uint32_t a, uint16_t v) { asm volatile("st.shared.u16 [%0], %1;" ::"r"(a), "h"(v) : "memory"); }
__device__ __forceinline__ void ldsm4(uint32_t* r, uint32_t a) {
    asm volatile("ldmatrix.sync.aligned.m8n8.x4.shared.b16 {%0,%1,%2,%3}, [%4];"
                 : "=r"(r[0]), "=r"(r[1]), "=r"(r[2]), "=r"(r[3]) : "r"(a) : "memory");
}
__device__ __forceinline__ void ldsm4t(uint32_t* r, uint32_t a) {
    asm volatile("ldmatrix.sync.aligned.m8n8.x4.trans.shared.b16 {%0,%1,%2,%3}, [%4];"
                 : "=r"(r[0]), "=r"(r[1]), "=r"(r[2]), "=r"(r[3]) : "r"(a) : "memory");
}
__device__ __forceinline__ void mma16816(float* d, const uint32_t* a, uint32_t b0, uint32_t b1) {
    asm("mma.sync.aligned.m16n8k16.row.col.f32.bf16.bf16.f32 {%0,%1,%2,%3}, {%4,%5,%6,%7}, {%8,%9}, {%0,%1,%2,%3};"
        : "+f"(d[0]), "+f"(d[1]), "+f"(d[2]), "+f"(d[3])
        : "r"(a[0]), "r"(a[1]), "r"(a[2]), "r"(a[3]), "r"(b0), "r"(b1));
}
__device__ __forceinline__ float ex2(float x) { float y; asm("ex2.approx.ftz.f32 %0, %1;" : "=f"(y) : "f"(x)); return y; }
__device__ __forceinline__ float F(uint32_t u) { return __uint_as_float(u); }
__device__ __forceinline__ uint32_t pack_bf16(float lo, float hi) {
    uint32_t r;
    asm("cvt.rn.bf16x2.f32 %0, %1, %2;" : "=r"(r) : "f"(hi), "f"(lo));
    return r;
}
#define POLL_LIMIT (1 << 18)
__device__ __forceinline__ uint32_t clk() { uint32_t c; asm volatile("mov.u32 %0, %%clock;" : "=r"(c)); return c; }
__device__ __forceinline__ void wait_until(uint32_t c0, uint32_t d) { while (clk() - c0 < d) { } }
__device__ __forceinline__ uint32_t bad(const uint4& a, uint32_t tag) { return (a.x ^ tag) | (a.z ^ tag); }
__device__ __forceinline__ uint32_t bad(const uint2& a, uint32_t tag) { return a.x ^ tag; }
template <int N, int S, typename V>
__device__ __forceinline__ void issue(V* v, const float* p) {
#pragma unroll
    for (int i = 0; i < N; i++) ldx(v[i], p + i * S);
}
template <int N, typename V>
__device__ __forceinline__ bool missing(const V* v, uint32_t tag) {
    uint32_t any = 0;
#pragma unroll
    for (int i = 0; i < N; i++) any |= bad(v[i], tag);
    return __any_sync(~0u, (any & 3u) != 0);
}
template <int N>
__device__ __forceinline__ bool missing2(const uint2* a, const uint4* v, uint32_t tag) {
    uint32_t any = 0;
#pragma unroll
    for (int i = 0; i < N; i++) any |= bad(a[i], tag) | bad(v[i], tag);
    return __any_sync(~0u, (any & 3u) != 0);
}
__device__ __forceinline__ bool missing3(const uint2* a, const uint4* v, const uint4* u, uint32_t tag) {
    const uint32_t any = (bad(a[0], tag) | bad(a[1], tag)) | (bad(v[0], tag) | bad(v[1], tag)) | (bad(u[0], tag) | bad(u[1], tag));
    return __any_sync(~0u, (any & 3u) != 0);
}
__device__ __forceinline__ float rsq(float x) { float y; asm("rsqrt.approx.ftz.f32 %0, %1;" : "=f"(y) : "f"(x)); return y; }
template <int N, int S>
__device__ __forceinline__ void prewait(const float* p, uint32_t tag) {
    uint2 u[N];
#pragma unroll 1
    for (int n = 0; n < POLL_LIMIT; n++) {
        issue<N, S>(u, p);
        if (!missing<N>(u, tag)) break;
        __nanosleep(BACKOFF);
    }
}
template <int N, int S, typename V>
__device__ __forceinline__ void fetch(V* v, const float* p, uint32_t tag) {
    int n = 0;
#pragma unroll 1
    do { issue<N, S>(v, p); } while (missing<N>(v, tag) && ++n < POLL_LIMIT);
}
template <int N>
__device__ __forceinline__ float4 sum_v(const uint4* v) {
    if constexpr (N == 1) {
        return make_float4(F(v[0].x), F(v[0].y), F(v[0].z), F(v[0].w));
    } else {
        const float4 a = sum_v<N / 2>(v), b = sum_v<N / 2>(v + N / 2);
        return make_float4(a.x + b.x, a.y + b.y, a.z + b.z, a.w + b.w);
    }
}
__device__ __forceinline__ float4 ar43(float4 v) {
#pragma unroll
    for (int o = 16; o >= 8; o >>= 1) {
        v.x += __shfl_xor_sync(~0u, v.x, o); v.y += __shfl_xor_sync(~0u, v.y, o);
        v.z += __shfl_xor_sync(~0u, v.z, o); v.w += __shfl_xor_sync(~0u, v.w, o);
    }
    return v;
}
__device__ __forceinline__ int map_f(float v) { const int i = __float_as_int(v); return i ^ ((i >> 31) & 0x7fffffff); }
__device__ __forceinline__ float unmap_f(int i) { return __int_as_float(i ^ ((i >> 31) & 0x7fffffff)); }
constexpr float SM_SCALE = 0.08838834764831845f * 1.4426950408889634f;
__device__ __forceinline__ uint32_t next_tag(uint32_t tag) { return tag == 3u ? 1u : tag + 1u; }
__device__ __forceinline__ void sts_chunk(uint32_t a, const float4& v) {
    const uint32_t h0 = pack_bf16(v.x, v.z), h1 = pack_bf16(v.y, v.w);
    sts_v2(a, h0, h1);
    sts_v2(a + 64, pack_bf16(v.x - F(h0 << 16), v.z - F(h0 & 0xffff0000u)), pack_bf16(v.y - F(h1 << 16), v.w - F(h1 & 0xffff0000u)));
}

#define TR(i) do { } while (0)

__global__ void __launch_bounds__(NTHREADS, 1)
fused_decode_kernel(const __grid_constant__ Maps maps, const __nv_bfloat16* __restrict__ x0,
                    const __nv_bfloat16* __restrict__ wq, __nv_bfloat16* __restrict__ out) {
    extern __shared__ __align__(1024) unsigned char smem_raw[];
    const uint32_t sb = smem_u32(smem_raw);
    const int b0_ = blockIdx.x, t0_ = threadIdx.x;
    const int wg = __shfl_sync(0xffffffffu, t0_ >> 7, 0);
    if (wg == 2) {
        asm volatile("setmaxnreg.dec.sync.aligned.u32 40;");
        const int b = b0_, w = t0_ >> 5, lane = t0_ & 31;
        const uint32_t bars = sb + SM_BAR;
        float* gs = g_s;
        if (w == 8) {
            unsigned long long g0;
            asm volatile("mov.u64 %0, %%globaltimer;" : "=l"(g0));
            const int stag = (b >> 4) * STAG / 8 + (b & 15) * STAG2 / 16;
            auto pace = [&](int slot16) {
                const long long tgt = (long long)(slot16 * TAU / 16 + TOFF + stag);
                unsigned long long g;
                do { asm volatile("mov.u64 %0, %%globaltimer;" : "=l"(g)); } while ((long long)(g - g0) < tgt);
            };
            const int kvrow = (b >> 4) * SK + (SK - WIN) + (b & 15) * 256;
            auto kvchunk = [&](int c) {
                const CUtensorMap* m = (c >> 2) ? &maps.v : &maps.k;
                const uint32_t dst = sb + SM_K + (c >> 2) * 65536 + (c & 3) * 8192;
                mbar_expect_tx(bars + 8 * c, 16384);
                tma2d(dst, m, 0, kvrow + (c & 3) * 64, bars + 8 * c);
                tma2d(dst + 32768, m, 64, kvrow + (c & 3) * 64, bars + 8 * c);
            };
            if (lane == 0) {
#pragma unroll 1
                for (int c = 0; c < EARLY; c++) { mbar_init(bars + 8 * c, 1); init_fence(); kvchunk(c); }
            }
            __syncwarp();
            bar_sync<NB_SVC, 128>();
            asm volatile("bar.arrive %0, 384;" ::"n"(NB_INIT) : "memory");
            if (lane == 0) {
#pragma unroll 1
                for (int c = EARLY; c < 8; c++) {
                    if (c >= DEPTH) mbar_wait(bars + 8 * (c - DEPTH));
                    pace(c * 16);
                    kvchunk(c);
                }
                const unsigned long long g1 = g0 + T8;
                mbar_expect_tx(bars + 8 * MB_WO, 32768);
                mbar_expect_tx(bars + 8 * MB_W13A, 16384);
                mbar_expect_tx(bars + 8 * MB_W13, 16384);
                mbar_expect_tx(bars + 8 * MB_W2, 14336);
#pragma unroll 1
                for (int i = 0; i < 10; i++) {
                    const int ph = (i < 4 ? (b >> 2) * (STAG3 / 32) : i < 8 ? (b & 7) * (STAG3 / 8) : (b >> 3) * (STAG3 / 16));
                    unsigned long long g;
                    do { asm volatile("mov.u64 %0, %%globaltimer;" : "=l"(g)); } while ((long long)(g - g1) < (long long)((i & ~1) * (TAU2 / 2) + ph));
                    const int lo = i & 1, hi = (i >> 1) & 1;
                    if (i < 4) {
                        tma2d(sb + SM_WO + lo * 16384 + hi * 8192, &maps.wo, (b & 3) * 128 + lo * 64, (b >> 2) * 128 + hi * 64, bars + 8 * MB_WO);
                    } else if (i < 8) {
                        if (i == 4) mbar_wait(bars + 8 * MB_KFREE);
                        tma2d(sb + SM_W1 + lo * 16384 + hi * 8192, lo ? &maps.w3 : &maps.w1, (b >> 3) * 112 + hi * 64, (b & 7) * 64, bars + 8 * (hi ? MB_W13 : MB_W13A));
                    } else {
                        tma2d(sb + SM_W2 + lo * 7168, &maps.w2, (b & 7) * 64, (b >> 3) * 112 + lo * 56, bars + 8 * MB_W2);
                    }
                }
            }
            return;
        }
        if (lane == 0) {
#pragma unroll 1
            for (int i = EARLY + (w - 9); i <= MB_W13A; i += 3) mbar_init(bars + 8 * i, i == MB_KFREE ? 8 : 1);
            init_fence();
            if (w == 10) sts_f(sb + SM_STOP, 0.f);
        } else if (w == 11 && lane < 6) {
            asm volatile("prefetch.tensormap [%0];" ::"l"((uint64_t)(&maps.k + lane)) : "memory");
        }
        const unsigned ep = ldg_u32(gs + O_EPOCH);
        __syncwarp();
        bar_sync<NB_SVC, 128>();
        bar_sync<NB_INIT, 384>();
        uint32_t tag = (2u * ep) % 3u + 1u;
        if (w == 9) {
#pragma unroll 1
            for (int i = 0; i < 4; ++i) {
                bar_sync<NB_BX, 288>();
                const bool ffn = i & 1;
                const float piv = lds_f(sb + (ffn ? SM_XR2 : SM_XR));
                float4 v = make_float4(piv, piv, piv, piv);
                if (ffn) { const float2 u = lds_f2(sb + SM_XR2 + lane * 8); v.x = u.x; v.y = u.y; }
                else v = lds_f4(sb + SM_XR + lane * 16);
                const float a = v.x - piv, bq = v.y - piv, cq = v.z - piv, d = v.w - piv;
                float s1 = (a + bq) + (cq + d), s2 = (a * a + bq * bq) + (cq * cq + d * d);
#pragma unroll
                for (int o = 16; o >= 1; o >>= 1) {
                    s1 += __shfl_xor_sync(~0u, s1, o);
                    s2 += __shfl_xor_sync(~0u, s2, o);
                }
                const float n = ffn ? 64.f : 128.f;
                if (lane < 4) stx1(gs + b * PB + (ffn ? O_STF : O_STQ) + lane * 2, fmaf(n, piv, s1), fmaxf(s2 - s1 * s1 / n, 0.f), tag);
                if (ffn) tag = next_tag(tag);
            }
        } else if (w == 10) {
        } else {
#pragma unroll 1
            for (int it = 0; it < 2; ++it) {
                bar_sync<NB_P, 288>();
                const float M = unmap_f(__float_as_int(lds_f(sb + SM_MW + it * 16 + (lane & 3) * 4))) * SM_SCALE;
                const float4 l0 = lds_f4(sb + SM_LP + lane * 32), l1 = lds_f4(sb + SM_LP + lane * 32 + 16);
                float l = ((l0.x + l0.y) + (l0.z + l0.w)) + ((l1.x + l1.y) + (l1.z + l1.w));
                l += __shfl_xor_sync(~0u, l, 4);
                l += __shfl_xor_sync(~0u, l, 8);
                l += __shfl_xor_sync(~0u, l, 16);
                if (lane < 4) stx1(gs + b * PB + O_ML + lane * 2, l, M, tag);
                tag = next_tag(tag);
            }
        }
        return;
    }

    {
        const int b = b0_, t = t0_;
        const int hq = (b >> 4) * 4 + ((b >> 3) & 1) * 2 + (b & 1);
        const __nv_bfloat16* src = wq + (size_t)(((b >> 1) & 3) * 128 + (t >> 4)) * 4096 + hq * 128 + (t & 15) * 8;
        const uint32_t dst = sb + SM_WQ + ((t >> 3) & 1) * 16384 + (t >> 4) * 128 + (((t & 7) ^ ((t >> 4) & 7)) << 4);
#pragma unroll
        for (int i = 0; i < 8; i++)
            asm volatile("cp.async.cg.shared.global [%0], [%1], 16;" ::"r"(dst + i * 2048), "l"(src + (size_t)i * 16 * 4096) : "memory");
        asm volatile("cp.async.commit_group;" ::: "memory");
        stx2(g_s + b * PB + t * 4, 0.f, 0.f, 0.f, 0.f, 0u);
        if (t * 4 + 1024 < PB) stx2(g_s + b * PB + 1024 + t * 4, 0.f, 0.f, 0.f, 0.f, 0u);
    }
    asm volatile("setmaxnreg.inc.sync.aligned.u32 232;");
    float* const gs = g_s;
    const uint32_t bars = sb + SM_BAR;
    const unsigned ep = ldg_u32(gs + O_EPOCH);
    {
        const int b = b0_, t = t0_, w = t >> 5, lane = t & 31, g = lane >> 2, c = lane & 3, pl = lane >> 3, ch = lane & 7;
        const int kc = 32 * (w & 3) + (ch >> 2) * 16 + 2 * (ch & 3);
        const __nv_bfloat16* xp = x0 + ((b >> 1) & 3) * 128 + kc;
        const uint32_t x01 = *reinterpret_cast<const uint32_t*>(xp), x89 = *reinterpret_cast<const uint32_t*>(xp + 8);
        const uint32_t lt = ((lane & 7) + ((lane >> 4) & 1) * 8) * 128 + ((((w & 3) * 2 + ((lane >> 3) & 1)) ^ (lane & 7)) << 4);
        const uint32_t o_exp = b * PB + w * 16 + g * 2, o_ld = (w & 3) * 32 + ch * 4;
        const uint32_t a_xs = sb + SM_XS + (w & 3) * 256 + (ch & 3) * 16 + (ch >> 2) * 8;
        const int hA = 2 * (c & 1);
        const uint32_t tb = sb + SM_TAB + t * 16;
        sts_v4(tb, sb + SM_XS + (lane & 15) * 16, a_xs, sb + SM_XR + o_ld * 4,
               (lane < 8 ? 1u : 0u) | (lane < 16 ? 2u : 0u) | (c == 0 ? 4u : 0u) | (c == 1 ? 8u : 0u) | (c < 2 ? 16u : 0u) | ((g & 1) ? 32u : 0u) |
               ((b < 16 && w == ((b >> 3) * 2 + (b & 1)) && pl == 0) ? 64u : 0u) | ((lane >> 4) ? 128u : 0u) | (((lane >> 3) & 1) ? 256u : 0u) | ((c & 1) ? 512u : 0u) | (lane < 4 ? 1024u : 0u) | (w << 16));
        sts_v4(tb + 4096, O_RECA + (pl * 8 + (b & 6) + ((w >> 1) & 1)) * PB + (o_ld & 63), (c == 0 ? O_RECB : O_CSB) + o_exp,
               sb + SM_WQ + (w >> 2) * 16384 + lt, ((b >> 1) & 3) * 128 + kc);
        sts_v4(tb + 2 * 4096, ((b & ~15) + ((w >> 1) & 1) * 8 + (w & 1)) * PB, O_RECC + b * PB + hA * 128 + w * 16 + g * 2,
               sb + SM_QS + ((g >> 1) * 4 + (w & 3)) * 64 + c * 16 + (g & 1) * 8, c < 2 ? sb + SM_PS + w * 256 + (hA * 4 + (g >> 1)) * 16 + (g & 1) * 4 : sb + SM_DUMMY + 4 * g + 128);
        sts_v4(tb + 3 * 4096, c < 2 ? sb + SM_LP + ((w * 4 + hA) * 8 + g) * 4 : sb + SM_DUMMY + 4 * g, sb + SM_MW + c * 4, sb + SM_MW + hA * 4,
                 ((b & ~15) + pl) * PB + O_RECC + ((b >> 2) & 3) * 128 + o_ld);
        sts_v4(tb + 4 * 4096, ((b & ~15) + pl) * PB + O_ML + ((b >> 2) & 3) * 2, O_RECD + (pl * 4 + ((b >> 1) & 3)) * PB + (b & 1) * 64 + (o_ld & 63),
               (c == 0 ? O_RECE : O_CSE) + b * PB + w * 32 + g * 4, sb + SM_W1 + (w >> 2) * 8192 + lt);
        sts_v4(tb + 5 * 4096, ((b & ~7) + pl) * PB + O_RECE + w * 32 + ch * 4, O_RECA + b * PB + (w & 3) * 16 + g * 2,
               sb + SM_XS + XS_F2 + (((w >> 1) * 4 + ((lane >> 3) & 1)) * 4 + (ch >> 1)) * 16 + ((w & 1) * 4 + (lane >> 4) * 2 + (ch & 1)) * 2,
               sb + SM_XR2 + ((w & 3) * 4 + (g >> 1)) * 16 + (g & 1) * 8);
        if (w < 4) sts_v4(sb + SM_XR + o_ld * 4, x01 << 16, x89 << 16, x01 & 0xffff0000u, x89 & 0xffff0000u);
        if (t == 0) sts_v4(sb + SM_ONES, 0x3F803F80u, 0x3F803F80u, 0x3F803F80u, 0x3F803F80u);
        if (t < 2) sts_v4(sb + SM_MW + t * 16, 0x80000000u, 0x80000000u, 0x80000000u, 0x80000000u);
    }
    uint32_t kf[2][8][4], vf[16][4];

    bar_sync<NB_INIT, 384>();
    asm volatile("cp.async.wait_group 0;" ::: "memory");
    bar_sync<NB_B, 256>();
    const uint32_t tb = sb + SM_TAB + t0_ * 16;
    const uint4 cm = lds_v4(tb);
    const uint32_t a_bf = cm.x, a_xs = cm.y, a_xr = cm.z, fl = cm.w;
    const uint32_t w = fl >> 16;

    uint32_t tagp = 0;
    uint32_t tag = (2u * ep) % 3u + 1u;
    uint32_t c_out = clk();
#pragma unroll 1
    for (int it = 0; it < 3; ++it) {
        uint32_t wf[8][4];
        uint4 bb[4];
        const uint32_t exp_mask = it == 0 ? 12u : 4u;
        TR(0);
        {
            if (it == 2 && (b0_ >= 16 || w >= 4)) break;
            const uint4 k = lds_v4(tb + 4096);
#pragma unroll
            for (int s = 0; s < 8; s++) ldsm4t(wf[s], k.z + s * 2048);
#pragma unroll
            for (int i = 0; i < 4; i++) bb[i] = lds_v4(sb + SM_ONES);
            if (w < 4) {
                float4 xv = lds_f4(a_xr);
                if (it > 0) {
                    uint4 v[4];
                    wait_until(c_out, DLY);
                    TR(1);
                    fetch<4, 32 * PB>(v, gs + k.x, tagp);
                    TR(2);
                    xv = ar43(sum_v<4>(v));
                }
                sts_chunk(a_xs + XS_Q, xv);
                if (fl & 64u) {
                    *reinterpret_cast<uint32_t*>(out + k.w) = pack_bf16(xv.x, xv.z);
                    *reinterpret_cast<uint32_t*>(out + k.w + 8) = pack_bf16(xv.y, xv.w);
                }
                if (it == 2) break;
                sts_v4(a_xr, __float_as_uint(xv.x), __float_as_uint(xv.y), __float_as_uint(xv.z), __float_as_uint(xv.w));
            }
            bar_sync<NB_BX, 288>();
            float d0[4] = {0.f, 0.f, 0.f, 0.f}, d1[4] = {0.f, 0.f, 0.f, 0.f}, d2[4] = {0.f, 0.f, 0.f, 0.f}, d3[4] = {0.f, 0.f, 0.f, 0.f};
#pragma unroll
            for (int i = 0; i < 4; i++) lds_v4_if(bb[i], a_bf + XS_Q + i * 256, fl & 1u);
            TR(3);
#pragma unroll
            for (int i = 0; i < 4; i += 2) {
                mma16816(d0, wf[2 * i], bb[i].x, bb[i].y);
                mma16816(d1, wf[2 * i + 1], bb[i].z, bb[i].w);
                mma16816(d2, wf[2 * i + 2], bb[i + 1].x, bb[i + 1].y);
                mma16816(d3, wf[2 * i + 3], bb[i + 1].z, bb[i + 1].w);
            }
#pragma unroll
            for (int i = 0; i < 4; i++) d0[i] = (d0[i] + d1[i]) + (d2[i] + d3[i]);
            const float h = (fl & 4u) ? 1.f : 0.f;
            stx1_if(gs + k.y, fmaf(h, d0[1], d0[0]), fmaf(h, d0[3], d0[2]), tag, fl & exp_mask);
            c_out = clk();
            TR(4);
        }
        {
            const uint4 k = lds_v4(tb + 2 * 4096), k2 = lds_v4(tb + 3 * 4096);
            const uint32_t a_mx = k2.y + it * 16, a_mr = k2.z + it * 16;
            if (it == 0) {
                const int lane = t0_ & 31, i8 = lane & 7;
                const int key = (i8 + 8 * (i8 & 1)) ^ ((lane >> 3) & 1);
                mbar_wait(bars + 8 * (MB_K + (w >> 1)));
                mbar_wait(bars + 8 * (MB_K + 2));
#pragma unroll
                for (int T = 0; T < 2; T++) {
                    const uint32_t rowa = sb + SM_K + (w * 32 + T * 16 + key) * 128;
#pragma unroll
                    for (int s = 0; s < 8; s++)
                        ldsm4(kf[T][s], rowa + (s >> 2) * 32768 + ((((s & 3) * 2 + (lane >> 4)) ^ (key & 7)) << 4));
                }
            }
            if (w < 4) {
                const float* pb = gs + k.x;
                const float* pa = pb + O_RECB + (t0_ & 31) * 4;
                const uint32_t a_cq = sb + SM_XS + (t0_ >> 3) * 256 + 128 + (t0_ & 7) * 16;
                uint4 v[4];
                uint2 st[4];
                wait_until(c_out, DLY);
                TR(5);
                if (it == 0) {
                    uint4 cv[4];
                    fetch<4, 2 * PB>(cv, pa + (O_CSB - O_RECB), tag);
                    const float4 u = sum_v<4>(cv);
                    sts_v4(a_cq, __float_as_uint(u.x), __float_as_uint(u.y), __float_as_uint(u.z), __float_as_uint(u.w));
                }
                const float4 csq = lds_f4(a_cq);
                float rstd, mr;
                int n = 0;
#pragma unroll 1
                do {
                    issue<4, 2 * PB>(st, pb + O_STQ);
                    issue<4, 2 * PB>(v, pa);
                    const float mean4 = ((F(st[0].x) + F(st[1].x)) + (F(st[2].x) + F(st[3].x))) * 0.25f;
                    const float e0 = F(st[0].x) - mean4, e1 = F(st[1].x) - mean4, e2 = F(st[2].x) - mean4, e3 = F(st[3].x) - mean4;
                    const float m2 = ((F(st[0].y) + F(st[1].y)) + (F(st[2].y) + F(st[3].y))) + ((e0 * e0 + e1 * e1) + (e2 * e2 + e3 * e3)) * (1.f / 128.f);
                    rstd = rsq(m2 * (1.f / 512.f) + 1e-5f);
                    mr = -mean4 * (1.f / 128.f) * rstd;
                } while (missing2<4>(st, v, tag) && ++n < POLL_LIMIT);
                TR(6);
                const float4 q = sum_v<4>(v);
                sts_v2(k.z, pack_bf16(fmaf(q.x, rstd, mr * csq.x), fmaf(q.z, rstd, mr * csq.z)), pack_bf16(fmaf(q.y, rstd, mr * csq.y), fmaf(q.w, rstd, mr * csq.w)));
            }
            bar_sync<NB_B, 256>();
            float s00[4] = {0.f, 0.f, 0.f, 0.f}, s01[4] = {0.f, 0.f, 0.f, 0.f}, s10[4] = {0.f, 0.f, 0.f, 0.f}, s11[4] = {0.f, 0.f, 0.f, 0.f};
#pragma unroll
            for (int i = 0; i < 4; i++) lds_v4_if(bb[i], a_bf + (SM_QS - SM_XS) + i * 256, fl & 2u);
            TR(7);
#pragma unroll
            for (int i = 0; i < 4; i++) {
                mma16816(s00, kf[0][2 * i], bb[i].x, bb[i].y);
                mma16816(s10, kf[1][2 * i], bb[i].x, bb[i].y);
                mma16816(s01, kf[0][2 * i + 1], bb[i].z, bb[i].w);
                mma16816(s11, kf[1][2 * i + 1], bb[i].z, bb[i].w);
            }
#pragma unroll
            for (int i = 0; i < 4; i++) { s00[i] += s01[i]; s10[i] += s11[i]; }
            {
                const bool c0 = fl & 4u, c1 = fl & 8u, val = fl & 16u, hi = fl & 512u;
                const int iA = map_f(fmaxf(fmaxf(s00[0], s00[2]), fmaxf(s10[0], s10[2])));
                const int iB = map_f(fmaxf(fmaxf(s00[1], s00[3]), fmaxf(s10[1], s10[3])));
                const int m0 = __reduce_max_sync(~0u, c0 ? iA : (int)0x80000000), m1 = __reduce_max_sync(~0u, c0 ? iB : (int)0x80000000);
                const int m2 = __reduce_max_sync(~0u, c1 ? iA : (int)0x80000000), m3 = __reduce_max_sync(~0u, c1 ? iB : (int)0x80000000);
                const int mc = val ? (hi ? m1 : m0) : (hi ? m3 : m2);
                asm volatile("{\n.reg .pred q;\nsetp.ne.u32 q, %2, 0;\n@q red.shared.max.s32 [%0], %1;\n}" ::"r"(a_mx), "r"(mc), "r"(fl & 1024u) : "memory");
            }
            bar_sync<NB_B, 256>();
            const float2 mm = lds_f2(a_mr);
            const float mA = unmap_f(__float_as_int(mm.x)) * SM_SCALE, mB = unmap_f(__float_as_int(mm.y)) * SM_SCALE;
            const bool od = fl & 32u;
            const float pA0 = ex2(fmaf(od ? s00[2] : s00[0], SM_SCALE, -mA)), pA1 = ex2(fmaf(od ? s00[0] : s00[2], SM_SCALE, -mA));
            const float pA2 = ex2(fmaf(od ? s10[2] : s10[0], SM_SCALE, -mA)), pA3 = ex2(fmaf(od ? s10[0] : s10[2], SM_SCALE, -mA));
            const float pB0 = ex2(fmaf(od ? s00[3] : s00[1], SM_SCALE, -mB)), pB1 = ex2(fmaf(od ? s00[1] : s00[3], SM_SCALE, -mB));
            const float pB2 = ex2(fmaf(od ? s10[3] : s10[1], SM_SCALE, -mB)), pB3 = ex2(fmaf(od ? s10[1] : s10[3], SM_SCALE, -mB));
            sts_f(k.w, F(pack_bf16(pA0, pA1)));
            sts_f(k.w + 8, F(pack_bf16(pA2, pA3)));
            sts_f(k.w + 64, F(pack_bf16(pB0, pB1)));
            sts_f(k.w + 72, F(pack_bf16(pB2, pB3)));
            sts_f(k2.x, (pA0 + pA1) + (pA2 + pA3));
            sts_f(k2.x + 32, (pB0 + pB1) + (pB2 + pB3));
            if (it == 0) {
                if ((t0_ & 31) == 0) mbar_arrive(bars + 8 * MB_KFREE);
                const uint32_t a0 = lds_v4(tb + 4096).z + (SM_V - SM_WQ) + (w >> 2) * 16384;
#pragma unroll
                for (int hf = 0; hf < 4; hf++) {
                    mbar_wait(bars + 8 * (MB_V + hf));
#pragma unroll
                    for (int s = 0; s < 4; s++) ldsm4t(vf[hf * 4 + s], a0 + (hf * 4 + s) * 2048);
                }
            }
            uint4 bc[4];
#pragma unroll
            for (int i = 0; i < 4; i++) bc[i] = lds_v4(sb + SM_ONES);
            TR(8);
            bar_sync<NB_P, 288>();
            float acc[4][4];
#pragma unroll
            for (int i = 0; i < 4; i++) acc[i][0] = acc[i][1] = acc[i][2] = acc[i][3] = 0.f;
#pragma unroll
            for (int i = 0; i < 4; i++) lds_v4_if(bb[i], a_bf + (SM_PS - SM_XS) + i * 256, fl & 2u);
#pragma unroll
            for (int i = 0; i < 4; i++) lds_v4_if(bc[i], a_bf + (SM_PS - SM_XS) + (4 + i) * 256, fl & 2u);
            TR(9);
#pragma unroll
            for (int i = 0; i < 4; i++) {
                mma16816(acc[(2 * i) & 3], vf[2 * i], bb[i].x, bb[i].y);
                mma16816(acc[(2 * i + 1) & 3], vf[2 * i + 1], bb[i].z, bb[i].w);
            }
#pragma unroll
            for (int i = 0; i < 4; i++) {
                mma16816(acc[(2 * i) & 3], vf[8 + 2 * i], bc[i].x, bc[i].y);
                mma16816(acc[(2 * i + 1) & 3], vf[8 + 2 * i + 1], bc[i].z, bc[i].w);
            }
#pragma unroll
            for (int i = 0; i < 4; i++) acc[0][i] = (acc[0][i] + acc[1][i]) + (acc[2][i] + acc[3][i]);
            stx1_if(gs + k.y, acc[0][0], acc[0][2], tag, fl & 16u);
            stx1_if(gs + k.y + 128, acc[0][1], acc[0][3], tag, fl & 16u);
            c_out = clk();
            TR(10);
        }
        {
            const uint4 k = lds_v4(tb + 4096), k4 = lds_v4(tb + 4 * 4096);
            const uint32_t o_c = lds_v4(tb + 3 * 4096).w;
#pragma unroll
            for (int s = 0; s < 8; s++) ldsm4t(wf[s], k.z + (SM_WO - SM_WQ) + s * 2048);
            if (w < 4) {
                uint4 v[4];
                uint2 ml[4];
                float w0, w1, w2, w3;
                wait_until(c_out, DLY);
                if ((PW & 1) && it == 0) { if (w == 0) prewait<4, 4 * PB>(gs + k4.x, tag); bar_sync<NB_LD, 128>(); }
                TR(11);
                int n = 0;
#pragma unroll 1
                do {
                    issue<4, 4 * PB>(ml, gs + k4.x);
                    issue<4, 4 * PB>(v, gs + o_c);
                    float M = fmaxf(fmaxf(F(ml[0].y), F(ml[1].y)), fmaxf(F(ml[2].y), F(ml[3].y)));
                    M = fmaxf(M, __shfl_xor_sync(~0u, M, 8));
                    M = fmaxf(M, __shfl_xor_sync(~0u, M, 16));
                    w0 = ex2(F(ml[0].y) - M); w1 = ex2(F(ml[1].y) - M); w2 = ex2(F(ml[2].y) - M); w3 = ex2(F(ml[3].y) - M);
                    float L = fmaf(w0, F(ml[0].x), w1 * F(ml[1].x)) + fmaf(w2, F(ml[2].x), w3 * F(ml[3].x));
                    L += __shfl_xor_sync(~0u, L, 8);
                    L += __shfl_xor_sync(~0u, L, 16);
                    const float inv = __fdividef(1.f, L);
                    w0 *= inv; w1 *= inv; w2 *= inv; w3 *= inv;
                } while (missing2<4>(ml, v, tag) && ++n < POLL_LIMIT);
                TR(12);
                float4 o;
                o.x = fmaf(w0, F(v[0].x), w1 * F(v[1].x)) + fmaf(w2, F(v[2].x), w3 * F(v[3].x));
                o.y = fmaf(w0, F(v[0].y), w1 * F(v[1].y)) + fmaf(w2, F(v[2].y), w3 * F(v[3].y));
                o.z = fmaf(w0, F(v[0].z), w1 * F(v[1].z)) + fmaf(w2, F(v[2].z), w3 * F(v[3].z));
                o.w = fmaf(w0, F(v[0].w), w1 * F(v[1].w)) + fmaf(w2, F(v[2].w), w3 * F(v[3].w));
                sts_chunk(a_xs + XS_O, ar43(o));
            }
            if (it == 0) {
                mbar_wait(bars + 8 * MB_WO);
#pragma unroll
                for (int s = 0; s < 8; s++) ldsm4t(wf[s], k.z + (SM_WO - SM_WQ) + s * 2048);
            }
            bar_sync<NB_B, 256>();
            float d0[4] = {0.f, 0.f, 0.f, 0.f}, d1[4] = {0.f, 0.f, 0.f, 0.f}, d2[4] = {0.f, 0.f, 0.f, 0.f}, d3[4] = {0.f, 0.f, 0.f, 0.f};
#pragma unroll
            for (int i = 0; i < 4; i++) lds_v4_if(bb[i], a_bf + XS_O + i * 256, fl & 1u);
#pragma unroll
            for (int i = 0; i < 4; i += 2) {
                mma16816(d0, wf[2 * i], bb[i].x, bb[i].y);
                mma16816(d1, wf[2 * i + 1], bb[i].z, bb[i].w);
                mma16816(d2, wf[2 * i + 2], bb[i + 1].x, bb[i + 1].y);
                mma16816(d3, wf[2 * i + 3], bb[i + 1].z, bb[i + 1].w);
            }
#pragma unroll
            for (int i = 0; i < 4; i++) d0[i] = (d0[i] + d1[i]) + (d2[i] + d3[i]);
            stx1_if(gs + k.y + (O_RECD - O_RECB), d0[0] + d0[1], d0[2] + d0[3], tag, fl & 4u);
            c_out = clk();
            TR(13);
        }
        {
            const uint4 k = lds_v4(tb + 4 * 4096);
#pragma unroll
            for (int s = 0; s < 4; s++) { ldsm4t(wf[s], k.w + s * 2048); ldsm4t(wf[4 + s], k.w + 16384 + s * 2048); }
            bb[0] = lds_v4(sb + SM_ONES);
            bb[1] = lds_v4(sb + SM_ONES);
            if (w < 2) {
                const float4 xr = lds_f4(a_xr + (b0_ & 1) * 256);
                uint4 v[8];
                wait_until(c_out, DLY);
                if ((PW & 2) && it == 0) { if (w == 0) prewait<8, 16 * PB>(gs + (k.y & ~31u), tag); bar_sync<NB_LD, 64>(); }
                if (it == 0) mbar_wait(bars + 8 * DGATE);
                TR(14);
                fetch<8, 16 * PB>(v, gs + k.y, tag);
                TR(15);
                float4 x = ar43(sum_v<8>(v));
                x.x += xr.x; x.y += xr.y; x.z += xr.z; x.w += xr.w;
                sts_chunk(a_xs + XS_F1, x);
                sts_v4(a_xr + (SM_XR2 - SM_XR), __float_as_uint(x.x), __float_as_uint(x.y), __float_as_uint(x.z), __float_as_uint(x.w));
            }
            if (it == 0) {
                mbar_wait(bars + 8 * MB_W13A); mbar_wait(bars + 8 * MB_W13);
#pragma unroll
                for (int s = 0; s < 4; s++) { ldsm4t(wf[s], k.w + s * 2048); ldsm4t(wf[4 + s], k.w + 16384 + s * 2048); }
            }
            bar_sync<NB_BX, 288>();
            {
                float dg[4] = {0.f, 0.f, 0.f, 0.f}, du[4] = {0.f, 0.f, 0.f, 0.f};
                float dg1[4] = {0.f, 0.f, 0.f, 0.f}, du1[4] = {0.f, 0.f, 0.f, 0.f};
                lds_v4_if(bb[0], a_bf + XS_F1, fl & 1u);
                lds_v4_if(bb[1], a_bf + XS_F1 + 256, fl & 1u);
                mma16816(dg, wf[0], bb[0].x, bb[0].y);
                mma16816(du, wf[4], bb[0].x, bb[0].y);
                mma16816(dg1, wf[1], bb[0].z, bb[0].w);
                mma16816(du1, wf[5], bb[0].z, bb[0].w);
                mma16816(dg, wf[2], bb[1].x, bb[1].y);
                mma16816(du, wf[6], bb[1].x, bb[1].y);
                mma16816(dg1, wf[3], bb[1].z, bb[1].w);
                mma16816(du1, wf[7], bb[1].z, bb[1].w);
                const float h = (fl & 4u) ? 1.f : 0.f;
                const float g0 = fmaf(h, dg[1] + dg1[1], dg[0] + dg1[0]), g1 = fmaf(h, dg[3] + dg1[3], dg[2] + dg1[2]);
                const float u0 = fmaf(h, du[1] + du1[1], du[0] + du1[0]), u1 = fmaf(h, du[3] + du1[3], du[2] + du1[2]);
                stx2_if(gs + k.z, g0, g1, u0, u1, tag, w < 7 ? fl & exp_mask : 0u);
            }
            c_out = clk();
            TR(16);
        }
        {
            const uint4 k = lds_v4(tb + 5 * 4096);
            const uint32_t a0 = lds_v4(tb + 4 * 4096).w + (SM_W2 - SM_W1) - (w >> 2) * 8192;
#pragma unroll
            for (int s = 0; s < 7; s++) ldsm4t(wf[s], a0 + s * 2048);
            float2 xr = make_float2(0.f, 0.f);
            if (b0_ < 8) xr = lds_f2(k.w);
            if (w < 7) {
                const bool b4 = fl & 128u, b3 = fl & 256u;
                const float* pa = gs + k.x;
                const float* ps = gs + ((b0_ & ~7) + ((t0_ >> 3) & 3)) * PB + O_STF;
                uint4 v[2];
                uint2 st[2];
                wait_until(c_out, DLY);
                if ((PW & 4) && it == 0) { if (w == 0) prewait<2, 4 * PB>(ps, tag); bar_sync<NB_LD, 224>(); }
                TR(17);
                const uint32_t a_cs = sb + SM_CSF + t0_ * 8;
                float2 cs = lds_f2(a_cs);
                float rstd, mr;
                uint4 cv[2];
                const float* pc = pa + (it == 0 ? O_CSE - O_RECE : 0);
                int n = 0;
#pragma unroll 1
                do {
                    issue<2, 4 * PB>(st, ps);
                    issue<2, 4 * PB>(v, pa);
                    if (it == 0) issue<2, 4 * PB>(cv, pc); else { cv[0] = make_uint4(tag, 0u, tag, 0u); cv[1] = cv[0]; }
                    float S = F(st[0].x) + F(st[1].x);
                    S += __shfl_xor_sync(~0u, S, 8);
                    S += __shfl_xor_sync(~0u, S, 16);
                    const float e0 = F(st[0].x) - S * 0.125f, e1 = F(st[1].x) - S * 0.125f;
                    float m2 = (F(st[0].y) + F(st[1].y)) + (e0 * e0 + e1 * e1) * (1.f / 64.f);
                    m2 += __shfl_xor_sync(~0u, m2, 8);
                    m2 += __shfl_xor_sync(~0u, m2, 16);
                    rstd = rsq(m2 * (1.f / 512.f) + 1e-5f);
                    mr = -S * (1.f / 512.f) * rstd;
                } while (missing3(st, v, cv, tag) && ++n < POLL_LIMIT);
                if (it == 0) {
                    const float4 u = ar43(sum_v<2>(cv));
                    cs.x = b4 ? u.y : u.x;
                    cs.y = b4 ? u.w : u.z;
                    sts_v2(a_cs, __float_as_uint(cs.x), __float_as_uint(cs.y));
                }
                TR(18);
                const float4 u = ar43(sum_v<2>(v));
                const float G = fmaf(b4 ? u.y : u.x, rstd, mr * cs.x);
                const float U = fmaf(b4 ? u.w : u.z, rstd, mr * cs.y);
                const float hv = __fdividef(G, 1.f + ex2(-1.4426950408889634f * G)) * U;
                const uint32_t hh = pack_bf16(hv, 0.f), ll = pack_bf16(hv - F(hh << 16), 0.f);
                sts_u16(k.z, (uint16_t)(b3 ? ll : hh));
            }
            if (it == 0) {
                mbar_wait(bars + 8 * MB_W2);
#pragma unroll
                for (int s = 0; s < 7; s++) ldsm4t(wf[s], a0 + s * 2048);
            }
            bar_sync<NB_B, 256>();
            if (w < 4) {
                float d0[4] = {0.f, 0.f, 0.f, 0.f}, d1[4] = {0.f, 0.f, 0.f, 0.f}, d2[4] = {0.f, 0.f, 0.f, 0.f}, d3[4] = {0.f, 0.f, 0.f, 0.f};
#pragma unroll
                for (int i = 0; i < 4; i++) lds_v4_if(bb[i], a_bf + XS_F2 + i * 256, fl & 1u);
                mma16816(d0, wf[0], bb[0].x, bb[0].y);
                mma16816(d1, wf[1], bb[0].z, bb[0].w);
                mma16816(d2, wf[2], bb[1].x, bb[1].y);
                mma16816(d3, wf[3], bb[1].z, bb[1].w);
                mma16816(d0, wf[4], bb[2].x, bb[2].y);
                mma16816(d1, wf[5], bb[2].z, bb[2].w);
                mma16816(d2, wf[6], bb[3].x, bb[3].y);
#pragma unroll
                for (int i = 0; i < 4; i++) d0[i] = (d0[i] + d1[i]) + (d2[i] + d3[i]);
                stx1_if(gs + k.y, (d0[0] + d0[1]) + xr.x, (d0[2] + d0[3]) + xr.y, tag, fl & 4u);
            }
            c_out = clk();
            TR(19);
        }
        tagp = tag;
        tag = next_tag(tag);
    }
    if (b0_ == 0 && t0_ == 0) stg_u32(gs + O_EPOCH, ep == 2u ? 0u : ep + 1u);
}

typedef CUresult (*EncodeFn)(CUtensorMap*, CUtensorMapDataType, cuuint32_t, void*, const cuuint64_t*, const cuuint64_t*,
                             const cuuint32_t*, const cuuint32_t*, CUtensorMapInterleave, CUtensorMapSwizzle,
                             CUtensorMapL2promotion, CUtensorMapFloatOOBfill);

void make_map(EncodeFn enc, CUtensorMap* m, const void* p, uint64_t cols, uint64_t rows, uint32_t box_rows) {
    cuuint64_t dims[2] = {cols, rows};
    cuuint64_t strides[1] = {cols * 2};
    cuuint32_t box[2] = {64, box_rows};
    cuuint32_t es[2] = {1, 1};
    enc(m, CU_TENSOR_MAP_DATA_TYPE_BFLOAT16, 2, const_cast<void*>(p), dims, strides, box, es, CU_TENSOR_MAP_INTERLEAVE_NONE,
        CU_TENSOR_MAP_SWIZZLE_128B, CU_TENSOR_MAP_L2_PROMOTION_NONE, CU_TENSOR_MAP_FLOAT_OOB_FILL_NONE);
}

}

extern "C" void kernel_launch(void* const* d_in, const int* in_sizes, int n_in, void* d_out, int out_size) {
    (void)in_sizes; (void)n_in; (void)out_size;
    static EncodeFn enc = nullptr;
    if (!enc) {
        void* fn = nullptr;
        cudaDriverEntryPointQueryResult st;
        cudaGetDriverEntryPoint("cuTensorMapEncodeTiled", &fn, cudaEnableDefault, &st);
        enc = (EncodeFn)fn;
        cudaFuncSetAttribute(fused_decode_kernel, cudaFuncAttributeMaxDynamicSharedMemorySize, SM_TOTAL);
    }
    Maps maps;
    make_map(enc, &maps.k, d_in[1], 128, 8ull * SK, 64);
    make_map(enc, &maps.v, d_in[2], 128, 8ull * SK, 64);
    make_map(enc, &maps.wo, d_in[4], 512, 4096, 64);
    make_map(enc, &maps.w1, d_in[6], 1792, 512, 64);
    make_map(enc, &maps.w3, d_in[7], 1792, 512, 64);
    make_map(enc, &maps.w2, d_in[8], 512, 1792, 56);
    maps.p[0] = (const char*)d_in[2]; maps.p[1] = (const char*)d_in[4]; maps.p[2] = (const char*)d_in[6];
    maps.p[3] = (const char*)d_in[7]; maps.p[4] = (const char*)d_in[8];
    fused_decode_kernel<<<NCTA, NTHREADS, SM_TOTAL>>>(maps, (const __nv_bfloat16*)d_in[0], (const __nv_bfloat16*)d_in[3], (__nv_bfloat16*)d_out);
}
```

```cpp
#include <cuda_runtime.h>
#include <cuda_bf16.h>
#include <cuda.h>
#include <stdint.h>

#define KTRACE 0
#define DEPTH 4
#define TAU 660
#define TOFF 700
#define T8 6500
#define TAU2 760
#define DLY_Q 350
#define DLY_A 250
#define DLY_O 250
#define DLY_F1 450
#define DLY_F2 450

namespace {

constexpr int NCTA = 128;
constexpr int NTHREADS = 384;
constexpr int SK = 32768, WIN = 4096;

constexpr int SM_WQ = 0;
constexpr int SM_K = 32768;
constexpr int SM_V = 98304;
constexpr int SM_WO = 163840;
constexpr int SM_W1 = SM_K;
constexpr int SM_W2 = SM_K + 32768;
constexpr int SM_MISC = 196608;
constexpr int SM_XS = SM_MISC;
constexpr int XS_Q = 0, XS_O = 1024, XS_F1 = 2048, XS_F2 = 3072;
constexpr int SM_QS = SM_XS + 4096;
constexpr int SM_PS = SM_QS + 1024;
constexpr int SM_LP = SM_PS + 2048;
constexpr int SM_MW = SM_LP + 1024;
constexpr int SM_XR = SM_MW + 128;
constexpr int SM_XR2 = SM_XR + 512;
constexpr int SM_ONES = SM_XR2 + 256 + 16;
constexpr int SM_BAR = SM_ONES + 16;
constexpr int MB_K = 0, MB_V = 4, MB_WO = 8, MB_W13 = 10, MB_W2 = 11, MB_KFREE = 12, MB_W13A = 13;
constexpr int SM_TAB = SM_BAR + 128 + 96;
constexpr int SM_CSF = SM_V;
constexpr int SM_DUMMY = SM_TAB + 6 * 4096;
constexpr int SM_TOTAL = SM_DUMMY + 256;
static_assert(SM_TAB % 16 == 0 && SM_TOTAL <= 232448, "smem");
constexpr int NB_INIT = 1, NB_B = 2, NB_BX = 3, NB_P = 4, NB_SVC = 5, NB_LD = 6;

constexpr int O_RECA = 0;
constexpr int O_STQ = 64;
constexpr int O_ML = 96;
constexpr int O_RECB = 128;
constexpr int O_CSB = 256;
constexpr int O_RECD = 384;
constexpr int O_RECC = 512;
constexpr int O_RECE = 1024;
constexpr int O_STF = 1248;
constexpr int O_CSE = 1280;
constexpr int PB = 1504;
constexpr int O_EPOCH = NCTA * PB;
constexpr int O_END = O_EPOCH + 32;
__device__ __align__(1024) float g_s[O_END];

struct Maps { CUtensorMap k, v, wo, w1, w3, w2; };

__device__ __forceinline__ uint32_t smem_u32(const void* p) { return (uint32_t)__cvta_generic_to_shared(p); }
__device__ __forceinline__ void mbar_init(uint32_t bar, uint32_t cnt) {
    asm volatile("mbarrier.init.shared::cta.b64 [%0], %1;" ::"r"(bar), "r"(cnt) : "memory");
}
__device__ __forceinline__ void mbar_expect_tx(uint32_t bar, uint32_t bytes) {
    asm volatile("mbarrier.arrive.expect_tx.shared::cta.b64 _, [%0], %1;" ::"r"(bar), "r"(bytes) : "memory");
}
__device__ __forceinline__ void mbar_arrive(uint32_t bar) {
    asm volatile("mbarrier.arrive.shared::cta.b64 _, [%0];" ::"r"(bar) : "memory");
}
__device__ __forceinline__ bool mbar_try(uint32_t bar) {
    uint32_t ok;
    asm volatile("{\n.reg .pred p;\nmbarrier.try_wait.parity.shared::cta.b64 p, [%1], 0;\nselp.u32 %0, 1, 0, p;\n}"
                 : "=r"(ok) : "r"(bar) : "memory");
    return ok != 0;
}
__device__ __forceinline__ bool mbar_test(uint32_t bar) {
    uint32_t ok;
    asm volatile("{\n.reg .pred p;\nmbarrier.test_wait.parity.shared::cta.b64 p, [%1], 0;\nselp.u32 %0, 1, 0, p;\n}"
                 : "=r"(ok) : "r"(bar) : "memory");
    return ok != 0;
}
__device__ __forceinline__ void mbar_wait(uint32_t bar) {
    int n = 0;
#pragma unroll 1
    while (!mbar_try(bar) && ++n < (1 << 17)) { }
}
__device__ __forceinline__ void tma2d(uint32_t dst, const CUtensorMap* m, int c0, int c1, uint32_t bar) {
    asm volatile("cp.async.bulk.tensor.2d.shared::cluster.global.mbarrier::complete_tx::bytes [%0], [%1, {%3, %4}], [%2];"
                 ::"r"(dst), "l"((uint64_t)m), "r"(bar), "r"(c0), "r"(c1) : "memory");
}
template <int ID, int N> __device__ __forceinline__ void bar_sync() { asm volatile("bar.sync %0, %1;" ::"n"(ID), "n"(N) : "memory"); }
__device__ __forceinline__ void init_fence() {
    asm volatile("fence.mbarrier_init.release.cluster;" ::: "memory");
    asm volatile("fence.proxy.async.shared::cta;" ::: "memory");
}
__device__ __forceinline__ uint32_t ldg_u32(const void* p) {
    uint32_t v;
    asm volatile("ld.relaxed.gpu.global.u32 %0, [%1];" : "=r"(v) : "l"(p) : "memory");
    return v;
}
__device__ __forceinline__ void stg_u32(void* p, uint32_t v) {
    asm volatile("st.relaxed.gpu.global.u32 [%0], %1;" ::"l"(p), "r"(v) : "memory");
}
__device__ __forceinline__ void ldx(uint4& v, const void* p) {
    asm volatile("{\n.reg .b64 a, b;\nld.relaxed.gpu.global.v2.b64 {a, b}, [%4];\nmov.b64 {%0,%1}, a;\nmov.b64 {%2,%3}, b;\n}"
                 : "=r"(v.x), "=r"(v.y), "=r"(v.z), "=r"(v.w) : "l"(p) : "memory");
}
__device__ __forceinline__ void ldx(uint2& v, const void* p) {
    asm volatile("{\n.reg .b64 a;\nld.relaxed.gpu.global.b64 a, [%2];\nmov.b64 {%0,%1}, a;\n}" : "=r"(v.x), "=r"(v.y) : "l"(p) : "memory");
}
__device__ __forceinline__ uint32_t tagf(float v, uint32_t tag) { return (__float_as_uint(v) & ~3u) | tag; }
__device__ __forceinline__ void stx1(void* p, float a, float b, uint32_t tag) {
    asm volatile("{\n.reg .b64 a;\nmov.b64 a, {%1,%2};\nst.relaxed.gpu.global.b64 [%0], a;\n}"
                 ::"l"(p), "r"(tagf(a, tag)), "r"(__float_as_uint(b)) : "memory");
}
__device__ __forceinline__ void stx1_if(void* p, float a, float b, uint32_t tag, uint32_t q) {
    asm volatile("{\n.reg .pred q;\n.reg .b64 a;\nsetp.ne.u32 q, %3, 0;\nmov.b64 a, {%1,%2};\n@q st.relaxed.gpu.global.b64 [%0], a;\n}"
                 ::"l"(p), "r"(tagf(a, tag)), "r"(__float_as_uint(b)), "r"(q) : "memory");
}
__device__ __forceinline__ void stx2_if(void* p, float a, float b, float c, float d, uint32_t tag, uint32_t q) {
    asm volatile("{\n.reg .pred q;\n.reg .b64 a, b;\nsetp.ne.u32 q, %5, 0;\nmov.b64 a, {%1,%2};\nmov.b64 b, {%3,%4};\n@q st.relaxed.gpu.global.v2.b64 [%0], {a, b};\n}"
                 ::"l"(p), "r"(tagf(a, tag)), "r"(__float_as_uint(b)), "r"(tagf(c, tag)), "r"(__float_as_uint(d)), "r"(q) : "memory");
}
__device__ __forceinline__ void stx2(void* p, float a, float b, float c, float d, uint32_t tag) {
    asm volatile("{\n.reg .b64 a, b;\nmov.b64 a, {%1,%2};\nmov.b64 b, {%3,%4};\nst.relaxed.gpu.global.v2.b64 [%0], {a, b};\n}"
                 ::"l"(p), "r"(tagf(a, tag)), "r"(__float_as_uint(b)), "r"(tagf(c, tag)), "r"(__float_as_uint(d)) : "memory");
}
__device__ __forceinline__ void lds_v4_if(uint4& v, uint32_t a, uint32_t p) {
    asm volatile("{\n.reg .pred q;\nsetp.ne.u32 q, %5, 0;\n@q ld.shared.v4.u32 {%0,%1,%2,%3}, [%4];\n}"
                 : "+r"(v.x), "+r"(v.y), "+r"(v.z), "+r"(v.w) : "r"(a), "r"(p) : "memory");
}
__device__ __forceinline__ uint4 lds_v4(uint32_t a) {
    uint4 v;
    asm volatile("ld.shared.v4.u32 {%0,%1,%2,%3}, [%4];" : "=r"(v.x), "=r"(v.y), "=r"(v.z), "=r"(v.w) : "r"(a) : "memory");
    return v;
}
__device__ __forceinline__ void sts_v4(uint32_t a, uint32_t x, uint32_t y, uint32_t z, uint32_t w) {
    asm volatile("st.shared.v4.u32 [%0], {%1,%2,%3,%4};" ::"r"(a), "r"(x), "r"(y), "r"(z), "r"(w) : "memory");
}
__device__ __forceinline__ void sts_v2(uint32_t a, uint32_t x, uint32_t y) {
    asm volatile("st.shared.v2.u32 [%0], {%1,%2};" ::"r"(a), "r"(x), "r"(y) : "memory");
}
__device__ __forceinline__ float4 lds_f4(uint32_t a) {
    float4 v;
    asm volatile("ld.shared.v4.f32 {%0,%1,%2,%3}, [%4];" : "=f"(v.x), "=f"(v.y), "=f"(v.z), "=f"(v.w) : "r"(a) : "memory");
    return v;
}
__device__ __forceinline__ float2 lds_f2(uint32_t a) {
    float2 v;
    asm volatile("ld.shared.v2.f32 {%0,%1}, [%2];" : "=f"(v.x), "=f"(v.y) : "r"(a) : "memory");
    return v;
}
__device__ __forceinline__ float lds_f(uint32_t a) {
    float v;
    asm volatile("ld.shared.f32 %0, [%1];" : "=f"(v) : "r"(a) : "memory");
    return v;
}
__device__ __forceinline__ void sts_f(uint32_t a, float v) { asm volatile("st.shared.f32 [%0], %1;" ::"r"(a), "f"(v) : "memory"); }
__device__ __forceinline__ void sts_u16(uint32_t a, uint16_t v) { asm volatile("st.shared.u16 [%0], %1;" ::"r"(a), "h"(v) : "memory"); }
__device__ __forceinline__ void ldsm4(uint32_t* r, uint32_t a) {
    asm volatile("ldmatrix.sync.aligned.m8n8.x4.shared.b16 {%0,%1,%2,%3}, [%4];"
                 : "=r"(r[0]), "=r"(r[1]), "=r"(r[2]), "=r"(r[3]) : "r"(a) : "memory");
}
__device__ __forceinline__ void ldsm4t(uint32_t* r, uint32_t a) {
    asm volatile("ldmatrix.sync.aligned.m8n8.x4.trans.shared.b16 {%0,%1,%2,%3}, [%4];"
                 : "=r"(r[0]), "=r"(r[1]), "=r"(r[2]), "=r"(r[3]) : "r"(a) : "memory");
}
template <int N>
__device__ __forceinline__ void ldw(uint32_t (*wf)[4], uint32_t a) {
#pragma unroll
    for (int s = 0; s < N; s++) ldsm4t(wf[s], a + s * 2048);
}
__device__ __forceinline__ void mma16816(float* d, const uint32_t* a, uint32_t b0, uint32_t b1) {
    asm("mma.sync.aligned.m16n8k16.row.col.f32.bf16.bf16.f32 {%0,%1,%2,%3}, {%4,%5,%6,%7}, {%8,%9}, {%0,%1,%2,%3};"
        : "+f"(d[0]), "+f"(d[1]), "+f"(d[2]), "+f"(d[3])
        : "r"(a[0]), "r"(a[1]), "r"(a[2]), "r"(a[3]), "r"(b0), "r"(b1));
}
__device__ __forceinline__ float ex2(float x) { float y; asm("ex2.approx.ftz.f32 %0, %1;" : "=f"(y) : "f"(x)); return y; }
__device__ __forceinline__ float F(uint32_t u) { return __uint_as_float(u); }
__device__ __forceinline__ uint32_t pack_bf16(float lo, float hi) {
    uint32_t r;
    asm("cvt.rn.bf16x2.f32 %0, %1, %2;" : "=r"(r) : "f"(hi), "f"(lo));
    return r;
}
#define POLL_LIMIT (1 << 18)
__device__ __forceinline__ uint32_t clk() { uint32_t c; asm volatile("mov.u32 %0, %%clock;" : "=r"(c)); return c; }
__device__ __forceinline__ void wait_until(uint32_t c0, uint32_t d) { while (clk() - c0 < d) { } }
__device__ __forceinline__ uint32_t bad(const uint4& a, uint32_t tag) { return (a.x ^ tag) | (a.z ^ tag); }
__device__ __forceinline__ uint32_t bad(const uint2& a, uint32_t tag) { return a.x ^ tag; }
template <int N, int S, typename V>
__device__ __forceinline__ void issue(V* v, const float* p) {
#pragma unroll
    for (int i = 0; i < N; i++) ldx(v[i], p + i * S);
}
template <int N, typename V>
__device__ __forceinline__ bool missing(const V* v, uint32_t tag) {
    uint32_t any = 0;
#pragma unroll
    for (int i = 0; i < N; i++) any |= bad(v[i], tag);
    return __any_sync(~0u, (any & 3u) != 0);
}
template <int N>
__device__ __forceinline__ bool missing2(const uint2* a, const uint4* v, uint32_t tag) {
    uint32_t any = 0;
#pragma unroll
    for (int i = 0; i < N; i++) any |= bad(a[i], tag) | bad(v[i], tag);
    return __any_sync(~0u, (any & 3u) != 0);
}
__device__ __forceinline__ bool missing3(const uint2* a, const uint4* v, const uint4* u, uint32_t tag) {
    const uint32_t any = (bad(a[0], tag) | bad(a[1], tag)) | (bad(v[0], tag) | bad(v[1], tag)) | (bad(u[0], tag) | bad(u[1], tag));
    return __any_sync(~0u, (any & 3u) != 0);
}
__device__ __forceinline__ float rcp(float x) { float y; asm("rcp.approx.ftz.f32 %0, %1;" : "=f"(y) : "f"(x)); return y; }
__device__ __forceinline__ float rsq(float x) { float y; asm("rsqrt.approx.ftz.f32 %0, %1;" : "=f"(y) : "f"(x)); return y; }
template <int N, int S>
__device__ __forceinline__ void prewait(const float* p, uint32_t tag) {
    uint2 u[N];
#pragma unroll 1
    for (int n = 0; n < POLL_LIMIT; n++) {
        issue<N, S>(u, p);
        if (!missing<N>(u, tag)) break;
        __nanosleep(20);
    }
}
template <int N, int S, typename V>
__device__ __forceinline__ void fetch(V* v, const float* p, uint32_t tag) {
    int n = 0;
#pragma unroll 1
    do { issue<N, S>(v, p); } while (missing<N>(v, tag) && ++n < POLL_LIMIT);
}
template <int N>
__device__ __forceinline__ float4 sum_v(const uint4* v) {
    if constexpr (N == 1) {
        return make_float4(F(v[0].x), F(v[0].y), F(v[0].z), F(v[0].w));
    } else {
        const float4 a = sum_v<N / 2>(v), b = sum_v<N / 2>(v + N / 2);
        return make_float4(a.x + b.x, a.y + b.y, a.z + b.z, a.w + b.w);
    }
}
__device__ __forceinline__ float4 ar43(float4 v) {
#pragma unroll
    for (int o = 16; o >= 8; o >>= 1) {
        v.x += __shfl_xor_sync(~0u, v.x, o); v.y += __shfl_xor_sync(~0u, v.y, o);
        v.z += __shfl_xor_sync(~0u, v.z, o); v.w += __shfl_xor_sync(~0u, v.w, o);
    }
    return v;
}
__device__ __forceinline__ int map_f(float v) { const int i = __float_as_int(v); return i ^ ((i >> 31) & 0x7fffffff); }
__device__ __forceinline__ float unmap_f(int i) { return __int_as_float(i ^ ((i >> 31) & 0x7fffffff)); }
constexpr float SM_SCALE = 0.08838834764831845f * 1.4426950408889634f;
__device__ __forceinline__ uint32_t next_tag(uint32_t tag) { return tag == 3u ? 1u : tag + 1u; }
__device__ __forceinline__ void sts_chunk(uint32_t a, const float4& v) {
    const uint32_t h0 = pack_bf16(v.x, v.z), h1 = pack_bf16(v.y, v.w);
    sts_v2(a, h0, h1);
    sts_v2(a + 64, pack_bf16(v.x - F(h0 << 16), v.z - F(h0 & 0xffff0000u)), pack_bf16(v.y - F(h1 << 16), v.w - F(h1 & 0xffff0000u)));
}

#define TR(i) do { } while (0)

__global__ void __launch_bounds__(NTHREADS, 1)
fused_decode_kernel(const __grid_constant__ Maps maps, const __nv_bfloat16* __restrict__ x0,
                    const __nv_bfloat16* __restrict__ wq, __nv_bfloat16* __restrict__ out) {
    extern __shared__ __align__(1024) unsigned char smem_raw[];
    const uint32_t sb = smem_u32(smem_raw);
    const int b0_ = blockIdx.x, t0_ = threadIdx.x;
    const int wg = __shfl_sync(0xffffffffu, t0_ >> 7, 0);
    if (wg == 2) {
        asm volatile("setmaxnreg.dec.sync.aligned.u32 40;");
        const int b = b0_, w = t0_ >> 5, lane = t0_ & 31;
        const uint32_t bars = sb + SM_BAR;
        float* gs = g_s;
        if (w == 8) {
            unsigned long long g0;
            asm volatile("mov.u64 %0, %%globaltimer;" : "=l"(g0));
            const int stag = (b >> 4) * (TAU / 8);
            auto pace = [&](int slot16) {
                const long long tgt = (long long)(slot16 * TAU / 16 + TOFF + stag);
                unsigned long long g;
                do { asm volatile("mov.u64 %0, %%globaltimer;" : "=l"(g)); } while ((long long)(g - g0) < tgt);
            };
            const int kvrow = (b >> 4) * SK + (SK - WIN) + (b & 15) * 256;
            auto kvchunk = [&](int c) {
                const CUtensorMap* m = (c >> 2) ? &maps.v : &maps.k;
                const uint32_t dst = sb + SM_K + (c >> 2) * 65536 + (c & 3) * 8192;
                mbar_expect_tx(bars + 8 * c, 16384);
                tma2d(dst, m, 0, kvrow + (c & 3) * 64, bars + 8 * c);
                tma2d(dst + 32768, m, 64, kvrow + (c & 3) * 64, bars + 8 * c);
            };
            if (lane == 0) { mbar_init(bars, 1); init_fence(); kvchunk(0); }
            __syncwarp();
            bar_sync<NB_SVC, 128>();
            asm volatile("bar.arrive %0, 384;" ::"n"(NB_INIT) : "memory");
            if (lane == 0) {
#pragma unroll 1
                for (int c = 1; c < 8; c++) {
                    if (c >= DEPTH) mbar_wait(bars + 8 * (c - DEPTH));
                    pace(c * 16);
                    kvchunk(c);
                }
                const unsigned long long g1 = g0 + T8;
                mbar_expect_tx(bars + 8 * MB_WO, 32768);
                mbar_expect_tx(bars + 8 * MB_W13A, 16384);
                mbar_expect_tx(bars + 8 * MB_W13, 16384);
                mbar_expect_tx(bars + 8 * MB_W2, 14336);
#pragma unroll 1
                for (int i = 0; i < 10; i++) {
                    const int ph = i < 4 ? (b >> 2) * (TAU2 / 32) : i < 8 ? (b & 7) * (TAU2 / 8) : (b >> 3) * (TAU2 / 16);
                    unsigned long long g;
                    do { asm volatile("mov.u64 %0, %%globaltimer;" : "=l"(g)); } while ((long long)(g - g1) < (long long)((i & ~1) * (TAU2 / 2) + ph));
                    const int lo = i & 1, hi = (i >> 1) & 1;
                    if (i < 4) {
                        tma2d(sb + SM_WO + lo * 16384 + hi * 8192, &maps.wo, (b & 3) * 128 + lo * 64, (b >> 2) * 128 + hi * 64, bars + 8 * MB_WO);
                    } else if (i < 8) {
                        if (i == 4) mbar_wait(bars + 8 * MB_KFREE);
                        tma2d(sb + SM_W1 + lo * 16384 + hi * 8192, lo ? &maps.w3 : &maps.w1, (b >> 3) * 112 + hi * 64, (b & 7) * 64, bars + 8 * (hi ? MB_W13 : MB_W13A));
                    } else {
                        tma2d(sb + SM_W2 + lo * 7168, &maps.w2, (b & 7) * 64, (b >> 3) * 112 + lo * 56, bars + 8 * MB_W2);
                    }
                }
            }
            return;
        }
        if (lane == 0) {
#pragma unroll 1
            for (int i = 1 + (w - 9); i <= MB_W13A; i += 3) mbar_init(bars + 8 * i, i == MB_KFREE ? 8 : 1);
            init_fence();
        } else if (w == 11 && lane < 6) {
            asm volatile("prefetch.tensormap [%0];" ::"l"((uint64_t)(&maps.k + lane)) : "memory");
        }
        const unsigned ep = ldg_u32(gs + O_EPOCH);
        __syncwarp();
        bar_sync<NB_SVC, 128>();
        bar_sync<NB_INIT, 384>();
        uint32_t tag = (2u * ep) % 3u + 1u;
        if (w == 9) {
            float* const pq = gs + b * PB + O_STQ + (lane & 15) * 2;
            const uint32_t l16 = (lane & 15) * 16;
#pragma unroll 1
            for (int it = 0; it < 2; ++it) {
                {
                    bar_sync<NB_BX, 288>();
                    const float piv = lds_f(sb + SM_XR);
                    const float4 u = lds_f4(sb + SM_XR + l16), v = lds_f4(sb + SM_XR + 256 + l16);
                    const float a0 = u.x - piv, a1 = u.y - piv, a2 = u.z - piv, a3 = u.w - piv;
                    const float a4 = v.x - piv, a5 = v.y - piv, a6 = v.z - piv, a7 = v.w - piv;
                    float s1 = ((a0 + a1) + (a2 + a3)) + ((a4 + a5) + (a6 + a7));
                    float s2 = (fmaf(a0, a0, a1 * a1) + fmaf(a2, a2, a3 * a3)) + (fmaf(a4, a4, a5 * a5) + fmaf(a6, a6, a7 * a7));
#pragma unroll
                    for (int o = 8; o >= 1; o >>= 1) { s1 += __shfl_xor_sync(~0u, s1, o); s2 += __shfl_xor_sync(~0u, s2, o); }
                    stx1_if(pq, fmaf(128.f, piv, s1), fmaxf(fmaf(-s1 * (1.f / 128.f), s1, s2), 0.f), tag, lane < 16);
                }
                {
                    bar_sync<NB_BX, 288>();
                    const float piv = lds_f(sb + SM_XR2);
                    const float4 u = lds_f4(sb + SM_XR2 + (l16 & 127)), v = lds_f4(sb + SM_XR2 + 128 + (l16 & 127));
                    const float a0 = u.x - piv, a1 = u.y - piv, a2 = u.z - piv, a3 = u.w - piv;
                    const float a4 = v.x - piv, a5 = v.y - piv, a6 = v.z - piv, a7 = v.w - piv;
                    float s1 = ((a0 + a1) + (a2 + a3)) + ((a4 + a5) + (a6 + a7));
                    float s2 = (fmaf(a0, a0, a1 * a1) + fmaf(a2, a2, a3 * a3)) + (fmaf(a4, a4, a5 * a5) + fmaf(a6, a6, a7 * a7));
#pragma unroll
                    for (int o = 4; o >= 1; o >>= 1) { s1 += __shfl_xor_sync(~0u, s1, o); s2 += __shfl_xor_sync(~0u, s2, o); }
                    stx1_if(pq + (O_STF - O_STQ), fmaf(64.f, piv, s1), fmaxf(fmaf(-s1 * (1.f / 64.f), s1, s2), 0.f), tag, lane < 16);
                }
                tag = next_tag(tag);
            }
        } else if (w == 10) {
        } else {
#pragma unroll 1
            for (int it = 0; it < 2; ++it) {
                bar_sync<NB_P, 288>();
                const float M = unmap_f(__float_as_int(lds_f(sb + SM_MW + it * 16 + (lane & 3) * 4))) * SM_SCALE;
                const float4 l0 = lds_f4(sb + SM_LP + lane * 32), l1 = lds_f4(sb + SM_LP + lane * 32 + 16);
                float l = ((l0.x + l0.y) + (l0.z + l0.w)) + ((l1.x + l1.y) + (l1.z + l1.w));
                l += __shfl_xor_sync(~0u, l, 4);
                l += __shfl_xor_sync(~0u, l, 8);
                l += __shfl_xor_sync(~0u, l, 16);
                if (lane < 16) stx1(gs + b * PB + O_ML + lane * 2, l, M, tag);
                tag = next_tag(tag);
            }
        }
        return;
    }

    {
        const int b = b0_, t = t0_;
        const int hq = (b >> 4) * 4 + ((b >> 3) & 1) * 2 + (b & 1);
        const __nv_bfloat16* src = wq + (size_t)(((b >> 1) & 3) * 128 + (t >> 4)) * 4096 + hq * 128 + (t & 15) * 8;
        const uint32_t dst = sb + SM_WQ + ((t >> 3) & 1) * 16384 + (t >> 4) * 128 + (((t & 7) ^ ((t >> 4) & 7)) << 4);
#pragma unroll
        for (int i = 0; i < 8; i++)
            asm volatile("cp.async.cg.shared.global [%0], [%1], 16;" ::"r"(dst + i * 2048), "l"(src + (size_t)i * 16 * 4096) : "memory");
        asm volatile("cp.async.commit_group;" ::: "memory");
        stx2(g_s + b * PB + t * 4, 0.f, 0.f, 0.f, 0.f, 0u);
        if (t * 4 + 1024 < PB) stx2(g_s + b * PB + 1024 + t * 4, 0.f, 0.f, 0.f, 0.f, 0u);
    }
    asm volatile("setmaxnreg.inc.sync.aligned.u32 232;");
    float* const gs = g_s;
    const uint32_t bars = sb + SM_BAR;
    const unsigned ep = ldg_u32(gs + O_EPOCH);
    {
        const int b = b0_, t = t0_, w = t >> 5, lane = t & 31, g = lane >> 2, c = lane & 3, pl = lane >> 3, ch = lane & 7;
        const int kc = 32 * (w & 3) + (ch >> 2) * 16 + 2 * (ch & 3);
        const __nv_bfloat16* xp = x0 + ((b >> 1) & 3) * 128 + kc;
        const uint32_t x01 = *reinterpret_cast<const uint32_t*>(xp), x89 = *reinterpret_cast<const uint32_t*>(xp + 8);
        const uint32_t lt = ((lane & 7) + ((lane >> 4) & 1) * 8) * 128 + ((((w & 3) * 2 + ((lane >> 3) & 1)) ^ (lane & 7)) << 4);
        const uint32_t o_exp = b * PB + w * 16 + g * 2, o_ld = (w & 3) * 32 + ch * 4;
        const uint32_t a_xs = sb + SM_XS + (w & 3) * 256 + (ch & 3) * 16 + (ch >> 2) * 8;
        const int hA = 2 * (c & 1);
        const uint32_t tb = sb + SM_TAB + t * 16;
        sts_v4(tb, sb + SM_XS + (lane & 15) * 16, a_xs, sb + SM_XR + o_ld * 4,
               (lane < 8 ? 1u : 0u) | (lane < 16 ? 2u : 0u) | (c == 0 ? 4u : 0u) | (c == 1 ? 8u : 0u) | (c < 2 ? 16u : 0u) | ((g & 1) ? 32u : 0u) |
               ((b < 16 && w == ((b >> 3) * 2 + (b & 1)) && pl == 0) ? 64u : 0u) | ((lane >> 4) ? 128u : 0u) | (((lane >> 3) & 1) ? 256u : 0u) | ((c & 1) ? 512u : 0u) | (lane < 4 ? 1024u : 0u) | (w << 16));
        sts_v4(tb + 4096, O_RECA + (pl * 8 + (b & 6) + ((w >> 1) & 1)) * PB + (o_ld & 63), (c == 0 ? O_RECB : O_CSB) + o_exp,
               sb + SM_WQ + (w >> 2) * 16384 + lt, ((b >> 1) & 3) * 128 + kc);
        sts_v4(tb + 2 * 4096, ((b & ~15) + ((w >> 1) & 1) * 8 + (w & 1)) * PB, O_RECC + b * PB + hA * 128 + w * 16 + g * 2,
               sb + SM_QS + ((g >> 1) * 4 + (w & 3)) * 64 + c * 16 + (g & 1) * 8, c < 2 ? sb + SM_PS + w * 256 + (hA * 4 + (g >> 1)) * 16 + (g & 1) * 4 : sb + SM_DUMMY + 4 * g + 128);
        sts_v4(tb + 3 * 4096, c < 2 ? sb + SM_LP + ((w * 4 + hA) * 8 + g) * 4 : sb + SM_DUMMY + 4 * g, sb + SM_MW + c * 4, sb + SM_MW + hA * 4,
                 ((b & ~15) + pl) * PB + O_RECC + ((b >> 2) & 3) * 128 + o_ld);
        sts_v4(tb + 4 * 4096, ((b & ~15) + pl) * PB + O_ML + ((b >> 2) & 3) * 2, O_RECD + (pl * 4 + ((b >> 1) & 3)) * PB + (b & 1) * 64 + (o_ld & 63),
               (c == 0 ? O_RECE : O_CSE) + b * PB + w * 32 + g * 4, sb + SM_W1 + (w >> 2) * 8192 + lt);
        sts_v4(tb + 5 * 4096, ((b & ~7) + pl) * PB + O_RECE + w * 32 + ch * 4, O_RECA + b * PB + (w & 3) * 16 + g * 2,
               sb + SM_XS + XS_F2 + (((w >> 1) * 4 + ((lane >> 3) & 1)) * 4 + (ch >> 1)) * 16 + ((w & 1) * 4 + (lane >> 4) * 2 + (ch & 1)) * 2,
               sb + SM_XR2 + ((w & 3) * 4 + (g >> 1)) * 16 + (g & 1) * 8);
        if (w < 4) sts_v4(sb + SM_XR + o_ld * 4, x01 << 16, x89 << 16, x01 & 0xffff0000u, x89 & 0xffff0000u);
        if (t == 0) sts_v4(sb + SM_ONES, 0x3F803F80u, 0x3F803F80u, 0x3F803F80u, 0x3F803F80u);
        if (t < 2) sts_v4(sb + SM_MW + t * 16, 0x80000000u, 0x80000000u, 0x80000000u, 0x80000000u);
    }
    uint32_t kf[2][8][4], vf[16][4];

    bar_sync<NB_INIT, 384>();
    asm volatile("cp.async.wait_group 0;" ::: "memory");
    bar_sync<NB_B, 256>();
    const uint32_t tb = sb + SM_TAB + t0_ * 16;
    const uint4 cm = lds_v4(tb);
    const uint32_t a_bf = cm.x, a_xs = cm.y, a_xr = cm.z, fl = cm.w;
    const uint32_t w = fl >> 16;

    uint32_t tagp = 0;
    uint32_t tag = (2u * ep) % 3u + 1u;
    uint32_t c_out = clk();
#pragma unroll 1
    for (int it = 0; it < 3; ++it) {
        uint32_t wf[8][4];
        uint4 bb[4];
        const uint32_t exp_mask = it == 0 ? 12u : 4u;
        TR(0);
        {
            if (it == 2 && (b0_ >= 16 || w >= 4)) break;
            const uint4 k = lds_v4(tb + 4096);
            if (w < 4) {
                float4 xv;
                if (it > 0) {
                    uint4 v[4];
                    wait_until(c_out, DLY_Q);
                    TR(1);
                    int n = 0;
#pragma unroll 1
                    do {
                        issue<4, 32 * PB>(v, gs + k.x);
                        ldw<8>(wf, k.z);
#pragma unroll
                        for (int i = 0; i < 4; i++) bb[i] = lds_v4(sb + SM_ONES);
                    } while (missing<4>(v, tagp) && ++n < POLL_LIMIT);
                    TR(2);
                    xv = ar43(sum_v<4>(v));
                } else {
                    xv = lds_f4(a_xr);
                    ldw<8>(wf, k.z);
#pragma unroll
                    for (int i = 0; i < 4; i++) bb[i] = lds_v4(sb + SM_ONES);
                }
                sts_chunk(a_xs + XS_Q, xv);
                if (fl & 64u) {
                    *reinterpret_cast<uint32_t*>(out + k.w) = pack_bf16(xv.x, xv.z);
                    *reinterpret_cast<uint32_t*>(out + k.w + 8) = pack_bf16(xv.y, xv.w);
                }
                if (it == 2) break;
                sts_v4(a_xr, __float_as_uint(xv.x), __float_as_uint(xv.y), __float_as_uint(xv.z), __float_as_uint(xv.w));
            } else {
                ldw<8>(wf, k.z);
#pragma unroll
                for (int i = 0; i < 4; i++) bb[i] = lds_v4(sb + SM_ONES);
            }
            bar_sync<NB_BX, 288>();
            float d0[4] = {0.f, 0.f, 0.f, 0.f}, d1[4] = {0.f, 0.f, 0.f, 0.f}, d2[4] = {0.f, 0.f, 0.f, 0.f}, d3[4] = {0.f, 0.f, 0.f, 0.f};
#pragma unroll
            for (int i = 0; i < 4; i++) lds_v4_if(bb[i], a_bf + XS_Q + i * 256, fl & 1u);
            TR(3);
#pragma unroll
            for (int i = 0; i < 4; i += 2) {
                mma16816(d0, wf[2 * i], bb[i].x, bb[i].y);
                mma16816(d1, wf[2 * i + 1], bb[i].z, bb[i].w);
                mma16816(d2, wf[2 * i + 2], bb[i + 1].x, bb[i + 1].y);
                mma16816(d3, wf[2 * i + 3], bb[i + 1].z, bb[i + 1].w);
            }
#pragma unroll
            for (int i = 0; i < 4; i++) d0[i] = (d0[i] + d1[i]) + (d2[i] + d3[i]);
            const float h = (fl & 4u) ? 1.f : 0.f;
            stx1_if(gs + k.y, fmaf(h, d0[1], d0[0]), fmaf(h, d0[3], d0[2]), tag, fl & exp_mask);
            c_out = clk();
            TR(4);
        }
        {
            const uint4 k = lds_v4(tb + 2 * 4096), k2 = lds_v4(tb + 3 * 4096);
            const uint32_t a_mx = k2.y + it * 16, a_mr = k2.z + it * 16;
            if (it == 0) {
                const int lane = t0_ & 31, i8 = lane & 7;
                const int key = (i8 + 8 * (i8 & 1)) ^ ((lane >> 3) & 1);
                mbar_wait(bars + 8 * (MB_K + (w >> 1)));
                mbar_wait(bars + 8 * (MB_K + 2));
#pragma unroll
                for (int T = 0; T < 2; T++) {
                    const uint32_t rowa = sb + SM_K + (w * 32 + T * 16 + key) * 128;
#pragma unroll
                    for (int s = 0; s < 8; s++)
                        ldsm4(kf[T][s], rowa + (s >> 2) * 32768 + ((((s & 3) * 2 + (lane >> 4)) ^ (key & 7)) << 4));
                }
            }
            if (w < 4) {
                const float* pb = gs + k.x;
                const float* pa = pb + O_RECB + (t0_ & 31) * 4;
                const uint32_t a_cq = sb + SM_XS + (t0_ >> 3) * 256 + 128 + (t0_ & 7) * 16;
                uint4 v[4];
                uint2 st[4];
                wait_until(c_out, DLY_A);
                TR(5);
                if (it == 0) {
                    uint4 cv[4];
                    fetch<4, 2 * PB>(cv, pa + (O_CSB - O_RECB), tag);
                    const float4 u = sum_v<4>(cv);
                    sts_v4(a_cq, __float_as_uint(u.x), __float_as_uint(u.y), __float_as_uint(u.z), __float_as_uint(u.w));
                }
                const float4 csq = lds_f4(a_cq);
                float rstd, mr;
                int n = 0;
#pragma unroll 1
                do {
                    issue<4, 2 * PB>(st, pb + O_STQ);
                    issue<4, 2 * PB>(v, pa);
                    const float mean4 = ((F(st[0].x) + F(st[1].x)) + (F(st[2].x) + F(st[3].x))) * 0.25f;
                    const float e0 = F(st[0].x) - mean4, e1 = F(st[1].x) - mean4, e2 = F(st[2].x) - mean4, e3 = F(st[3].x) - mean4;
                    const float m2 = ((F(st[0].y) + F(st[1].y)) + (F(st[2].y) + F(st[3].y))) + ((e0 * e0 + e1 * e1) + (e2 * e2 + e3 * e3)) * (1.f / 128.f);
                    rstd = rsq(m2 * (1.f / 512.f) + 1e-5f);
                    mr = -mean4 * (1.f / 128.f) * rstd;
                } while (missing2<4>(st, v, tag + (rstd < -1.f ? 1u : 0u)) && ++n < POLL_LIMIT);
                TR(6);
                const float4 q = sum_v<4>(v);
                sts_v2(k.z, pack_bf16(fmaf(q.x, rstd, mr * csq.x), fmaf(q.z, rstd, mr * csq.z)), pack_bf16(fmaf(q.y, rstd, mr * csq.y), fmaf(q.w, rstd, mr * csq.w)));
            }
            bar_sync<NB_B, 256>();
            float s00[4] = {0.f, 0.f, 0.f, 0.f}, s01[4] = {0.f, 0.f, 0.f, 0.f}, s10[4] = {0.f, 0.f, 0.f, 0.f}, s11[4] = {0.f, 0.f, 0.f, 0.f};
#pragma unroll
            for (int i = 0; i < 4; i++) lds_v4_if(bb[i], a_bf + (SM_QS - SM_XS) + i * 256, fl & 2u);
            TR(7);
#pragma unroll
            for (int i = 0; i < 4; i++) {
                mma16816(s00, kf[0][2 * i], bb[i].x, bb[i].y);
                mma16816(s10, kf[1][2 * i], bb[i].x, bb[i].y);
                mma16816(s01, kf[0][2 * i + 1], bb[i].z, bb[i].w);
                mma16816(s11, kf[1][2 * i + 1], bb[i].z, bb[i].w);
            }
#pragma unroll
            for (int i = 0; i < 4; i++) { s00[i] += s01[i]; s10[i] += s11[i]; }
            {
                const bool c0 = fl & 4u, c1 = fl & 8u, val = fl & 16u, hi = fl & 512u;
                const int iA = map_f(fmaxf(fmaxf(s00[0], s00[2]), fmaxf(s10[0], s10[2])));
                const int iB = map_f(fmaxf(fmaxf(s00[1], s00[3]), fmaxf(s10[1], s10[3])));
                const int m0 = __reduce_max_sync(~0u, c0 ? iA : (int)0x80000000), m1 = __reduce_max_sync(~0u, c0 ? iB : (int)0x80000000);
                const int m2 = __reduce_max_sync(~0u, c1 ? iA : (int)0x80000000), m3 = __reduce_max_sync(~0u, c1 ? iB : (int)0x80000000);
                const int mc = val ? (hi ? m1 : m0) : (hi ? m3 : m2);
                asm volatile("{\n.reg .pred q;\nsetp.ne.u32 q, %2, 0;\n@q red.shared.max.s32 [%0], %1;\n}" ::"r"(a_mx), "r"(mc), "r"(fl & 1024u) : "memory");
            }
            bar_sync<NB_B, 256>();
            const float2 mm = lds_f2(a_mr);
            const float mA = unmap_f(__float_as_int(mm.x)) * SM_SCALE, mB = unmap_f(__float_as_int(mm.y)) * SM_SCALE;
            const bool od = fl & 32u;
            const float pA0 = ex2(fmaf(od ? s00[2] : s00[0], SM_SCALE, -mA)), pA1 = ex2(fmaf(od ? s00[0] : s00[2], SM_SCALE, -mA));
            const float pA2 = ex2(fmaf(od ? s10[2] : s10[0], SM_SCALE, -mA)), pA3 = ex2(fmaf(od ? s10[0] : s10[2], SM_SCALE, -mA));
            const float pB0 = ex2(fmaf(od ? s00[3] : s00[1], SM_SCALE, -mB)), pB1 = ex2(fmaf(od ? s00[1] : s00[3], SM_SCALE, -mB));
            const float pB2 = ex2(fmaf(od ? s10[3] : s10[1], SM_SCALE, -mB)), pB3 = ex2(fmaf(od ? s10[1] : s10[3], SM_SCALE, -mB));
            sts_f(k.w, F(pack_bf16(pA0, pA1)));
            sts_f(k.w + 8, F(pack_bf16(pA2, pA3)));
            sts_f(k.w + 64, F(pack_bf16(pB0, pB1)));
            sts_f(k.w + 72, F(pack_bf16(pB2, pB3)));
            sts_f(k2.x, (pA0 + pA1) + (pA2 + pA3));
            sts_f(k2.x + 32, (pB0 + pB1) + (pB2 + pB3));
            if (it == 0) {
                if ((t0_ & 31) == 0) mbar_arrive(bars + 8 * MB_KFREE);
                const uint32_t a0 = lds_v4(tb + 4096).z + (SM_V - SM_WQ) + (w >> 2) * 16384;
#pragma unroll
                for (int hf = 0; hf < 4; hf++) {
                    mbar_wait(bars + 8 * (MB_V + hf));
#pragma unroll
                    for (int s = 0; s < 4; s++) ldsm4t(vf[hf * 4 + s], a0 + (hf * 4 + s) * 2048);
                }
            }
            uint4 bc[4];
#pragma unroll
            for (int i = 0; i < 4; i++) bc[i] = lds_v4(sb + SM_ONES);
            TR(8);
            bar_sync<NB_P, 288>();
            float acc[4][4];
#pragma unroll
            for (int i = 0; i < 4; i++) acc[i][0] = acc[i][1] = acc[i][2] = acc[i][3] = 0.f;
#pragma unroll
            for (int i = 0; i < 4; i++) lds_v4_if(bb[i], a_bf + (SM_PS - SM_XS) + i * 256, fl & 2u);
#pragma unroll
            for (int i = 0; i < 4; i++) lds_v4_if(bc[i], a_bf + (SM_PS - SM_XS) + (4 + i) * 256, fl & 2u);
            TR(9);
#pragma unroll
            for (int i = 0; i < 4; i++) {
                mma16816(acc[(2 * i) & 3], vf[2 * i], bb[i].x, bb[i].y);
                mma16816(acc[(2 * i + 1) & 3], vf[2 * i + 1], bb[i].z, bb[i].w);
            }
#pragma unroll
            for (int i = 0; i < 4; i++) {
                mma16816(acc[(2 * i) & 3], vf[8 + 2 * i], bc[i].x, bc[i].y);
                mma16816(acc[(2 * i + 1) & 3], vf[8 + 2 * i + 1], bc[i].z, bc[i].w);
            }
#pragma unroll
            for (int i = 0; i < 4; i++) acc[0][i] = (acc[0][i] + acc[1][i]) + (acc[2][i] + acc[3][i]);
            stx1_if(gs + k.y, acc[0][0], acc[0][2], tag, fl & 16u);
            stx1_if(gs + k.y + 128, acc[0][1], acc[0][3], tag, fl & 16u);
            c_out = clk();
            TR(10);
        }
        {
            const uint4 k = lds_v4(tb + 4096), k4 = lds_v4(tb + 4 * 4096);
            const uint32_t o_c = lds_v4(tb + 3 * 4096).w;
            bool landed = it != 0;
            if (w < 4) {
                uint4 v[4];
                uint2 ml[4];
                float w0, w1, w2, w3;
                if (it == 0) {
                    if (w == 0) prewait<4, 4 * PB>(gs + k4.x, tag); bar_sync<NB_LD, 128>(); }
                int n = 0;
                landed = __all_sync(~0u, mbar_test(bars + 8 * MB_WO));
#pragma unroll 1
                do {
                    issue<4, 4 * PB>(ml, gs + k4.x);
                    wait_until(c_out, DLY_O);
                    TR(11);
                    issue<4, 4 * PB>(v, gs + o_c);
                    ldw<8>(wf, k.z + (SM_WO - SM_WQ));
                    float M = fmaxf(fmaxf(F(ml[0].y), F(ml[1].y)), fmaxf(F(ml[2].y), F(ml[3].y)));
                    M = fmaxf(M, __shfl_xor_sync(~0u, M, 8));
                    M = fmaxf(M, __shfl_xor_sync(~0u, M, 16));
                    w0 = ex2(F(ml[0].y) - M); w1 = ex2(F(ml[1].y) - M); w2 = ex2(F(ml[2].y) - M); w3 = ex2(F(ml[3].y) - M);
                    float L = fmaf(w0, F(ml[0].x), w1 * F(ml[1].x)) + fmaf(w2, F(ml[2].x), w3 * F(ml[3].x));
                    L += __shfl_xor_sync(~0u, L, 8);
                    L += __shfl_xor_sync(~0u, L, 16);
                    const float inv = rcp(L);
                    w0 *= inv; w1 *= inv; w2 *= inv; w3 *= inv;
                } while (missing2<4>(ml, v, tag + ((w0 + w1) + (w2 + w3) < -1.f ? 1u : 0u)) && ++n < POLL_LIMIT);
                TR(12);
                float4 o;
                o.x = fmaf(w0, F(v[0].x), w1 * F(v[1].x)) + fmaf(w2, F(v[2].x), w3 * F(v[3].x));
                o.y = fmaf(w0, F(v[0].y), w1 * F(v[1].y)) + fmaf(w2, F(v[2].y), w3 * F(v[3].y));
                o.z = fmaf(w0, F(v[0].z), w1 * F(v[1].z)) + fmaf(w2, F(v[2].z), w3 * F(v[3].z));
                o.w = fmaf(w0, F(v[0].w), w1 * F(v[1].w)) + fmaf(w2, F(v[2].w), w3 * F(v[3].w));
                sts_chunk(a_xs + XS_O, ar43(o));
            } else {
                ldw<8>(wf, k.z + (SM_WO - SM_WQ));
            }
            if (!landed) { mbar_wait(bars + 8 * MB_WO); ldw<8>(wf, k.z + (SM_WO - SM_WQ)); }
            bar_sync<NB_B, 256>();
            float d0[4] = {0.f, 0.f, 0.f, 0.f}, d1[4] = {0.f, 0.f, 0.f, 0.f}, d2[4] = {0.f, 0.f, 0.f, 0.f}, d3[4] = {0.f, 0.f, 0.f, 0.f};
#pragma unroll
            for (int i = 0; i < 4; i++) lds_v4_if(bb[i], a_bf + XS_O + i * 256, fl & 1u);
#pragma unroll
            for (int i = 0; i < 4; i += 2) {
                mma16816(d0, wf[2 * i], bb[i].x, bb[i].y);
                mma16816(d1, wf[2 * i + 1], bb[i].z, bb[i].w);
                mma16816(d2, wf[2 * i + 2], bb[i + 1].x, bb[i + 1].y);
                mma16816(d3, wf[2 * i + 3], bb[i + 1].z, bb[i + 1].w);
            }
#pragma unroll
            for (int i = 0; i < 4; i++) d0[i] = (d0[i] + d1[i]) + (d2[i] + d3[i]);
            stx1_if(gs + k.y + (O_RECD - O_RECB), d0[0] + d0[1], d0[2] + d0[3], tag, fl & 4u);
            c_out = clk();
            TR(13);
        }
        {
            const uint4 k = lds_v4(tb + 4 * 4096);
            if (w < 2) {
                float4 xr;
                uint4 v[8];
                wait_until(c_out, DLY_F1);
                if (it == 0) mbar_wait(bars + 8 * MB_W13A);
                TR(14);
                int n = 0;
#pragma unroll 1
                do {
                    issue<8, 16 * PB>(v, gs + k.y);
                    ldw<4>(wf, k.w); ldw<4>(wf + 4, k.w + 16384);
                    bb[0] = lds_v4(sb + SM_ONES);
                    bb[1] = lds_v4(sb + SM_ONES);
                    xr = lds_f4(a_xr + (b0_ & 1) * 256);
                } while (missing<8>(v, tag) && ++n < POLL_LIMIT);
                TR(15);
                float4 x = ar43(sum_v<8>(v));
                x.x += xr.x; x.y += xr.y; x.z += xr.z; x.w += xr.w;
                sts_chunk(a_xs + XS_F1, x);
                sts_v4(a_xr + (SM_XR2 - SM_XR), __float_as_uint(x.x), __float_as_uint(x.y), __float_as_uint(x.z), __float_as_uint(x.w));
            } else {
                ldw<4>(wf, k.w); ldw<4>(wf + 4, k.w + 16384);
                bb[0] = lds_v4(sb + SM_ONES);
                bb[1] = lds_v4(sb + SM_ONES);
            }
            if (it == 0) {
                mbar_wait(bars + 8 * MB_W13A); mbar_wait(bars + 8 * MB_W13);
                ldw<4>(wf, k.w); ldw<4>(wf + 4, k.w + 16384);
            }
            bar_sync<NB_BX, 288>();
            {
                float dg[4] = {0.f, 0.f, 0.f, 0.f}, du[4] = {0.f, 0.f, 0.f, 0.f};
                float dg1[4] = {0.f, 0.f, 0.f, 0.f}, du1[4] = {0.f, 0.f, 0.f, 0.f};
                lds_v4_if(bb[0], a_bf + XS_F1, fl & 1u);
                lds_v4_if(bb[1], a_bf + XS_F1 + 256, fl & 1u);
                mma16816(dg, wf[0], bb[0].x, bb[0].y);
                mma16816(du, wf[4], bb[0].x, bb[0].y);
                mma16816(dg1, wf[1], bb[0].z, bb[0].w);
                mma16816(du1, wf[5], bb[0].z, bb[0].w);
                mma16816(dg, wf[2], bb[1].x, bb[1].y);
                mma16816(du, wf[6], bb[1].x, bb[1].y);
                mma16816(dg1, wf[3], bb[1].z, bb[1].w);
                mma16816(du1, wf[7], bb[1].z, bb[1].w);
                const float h = (fl & 4u) ? 1.f : 0.f;
                const float g0 = fmaf(h, dg[1] + dg1[1], dg[0] + dg1[0]), g1 = fmaf(h, dg[3] + dg1[3], dg[2] + dg1[2]);
                const float u0 = fmaf(h, du[1] + du1[1], du[0] + du1[0]), u1 = fmaf(h, du[3] + du1[3], du[2] + du1[2]);
                stx2_if(gs + k.z, g0, g1, u0, u1, tag, w < 7 ? fl & exp_mask : 0u);
            }
            c_out = clk();
            TR(16);
        }
        {
            const uint4 k = lds_v4(tb + 5 * 4096);
            const uint32_t a0 = lds_v4(tb + 4 * 4096).w + (SM_W2 - SM_W1) - (w >> 2) * 8192;
            bool landed = it != 0;
            float2 xr = make_float2(0.f, 0.f);
            if (b0_ < 8) xr = lds_f2(k.w);
            if (w < 7) {
                const bool b4 = fl & 128u, b3 = fl & 256u;
                const float* pa = gs + k.x;
                const float* ps = gs + ((b0_ & ~7) + ((t0_ >> 3) & 3)) * PB + O_STF;
                uint4 v[2];
                uint2 st[2];
                wait_until(c_out, DLY_F2);
                TR(17);
                const uint32_t a_cs = sb + SM_CSF + t0_ * 8;
                float2 cs = lds_f2(a_cs);
                uint4 cv[2];
                const float* pc = pa + (it == 0 ? O_CSE - O_RECE : 0);
                int n = 0;
                landed = __all_sync(~0u, mbar_test(bars + 8 * MB_W2));
#pragma unroll 1
                do {
                    issue<2, 4 * PB>(st, ps);
                    issue<2, 4 * PB>(v, pa);
                    if (it == 0) issue<2, 4 * PB>(cv, pc); else { cv[0] = make_uint4(tag, 0u, tag, 0u); cv[1] = cv[0]; }
                    ldw<7>(wf, a0);
                } while (missing3(st, v, cv, tag) && ++n < POLL_LIMIT);
                TR(18);
                if (it == 0) {
                    const float4 u = ar43(sum_v<2>(cv));
                    cs.x = b4 ? u.y : u.x;
                    cs.y = b4 ? u.w : u.z;
                    sts_v2(a_cs, __float_as_uint(cs.x), __float_as_uint(cs.y));
                }
                const float4 u0 = sum_v<2>(v);
                float S = F(st[0].x) + F(st[1].x);
                float T = fmaf(fmaf(F(st[0].x), F(st[0].x), F(st[1].x) * F(st[1].x)), 1.f / 64.f, F(st[0].y) + F(st[1].y));
                float G = (b4 ? u0.y : u0.x) + __shfl_xor_sync(~0u, b4 ? u0.x : u0.y, 16);
                float U = (b4 ? u0.w : u0.z) + __shfl_xor_sync(~0u, b4 ? u0.z : u0.w, 16);
                S += __shfl_xor_sync(~0u, S, 16);
                T += __shfl_xor_sync(~0u, T, 16);
                S += __shfl_xor_sync(~0u, S, 8);
                T += __shfl_xor_sync(~0u, T, 8);
                G += __shfl_xor_sync(~0u, G, 8);
                U += __shfl_xor_sync(~0u, U, 8);
                const float mean = S * (1.f / 512.f);
                const float rstd = rsq(fmaxf(fmaf(-mean, mean, T * (1.f / 512.f)), 0.f) + 1e-5f);
                G = rstd * fmaf(-mean, cs.x, G);
                U = rstd * fmaf(-mean, cs.y, U);
                const float hv = G * rcp(1.f + ex2(-1.4426950408889634f * G)) * U;
                const uint32_t hh = pack_bf16(hv, 0.f), ll = pack_bf16(hv - F(hh << 16), 0.f);
                sts_u16(k.z, (uint16_t)(b3 ? ll : hh));
            } else {
                ldw<7>(wf, a0);
            }
            if (!landed) { mbar_wait(bars + 8 * MB_W2); ldw<7>(wf, a0); }
            bar_sync<NB_B, 256>();
            if (w < 4) {
                float d0[4] = {0.f, 0.f, 0.f, 0.f}, d1[4] = {0.f, 0.f, 0.f, 0.f}, d2[4] = {0.f, 0.f, 0.f, 0.f}, d3[4] = {0.f, 0.f, 0.f, 0.f};
#pragma unroll
                for (int i = 0; i < 4; i++) lds_v4_if(bb[i], a_bf + XS_F2 + i * 256, fl & 1u);
                mma16816(d0, wf[0], bb[0].x, bb[0].y);
                mma16816(d1, wf[1], bb[0].z, bb[0].w);
                mma16816(d2, wf[2], bb[1].x, bb[1].y);
                mma16816(d3, wf[3], bb[1].z, bb[1].w);
                mma16816(d0, wf[4], bb[2].x, bb[2].y);
                mma16816(d1, wf[5], bb[2].z, bb[2].w);
                mma16816(d2, wf[6], bb[3].x, bb[3].y);
#pragma unroll
                for (int i = 0; i < 4; i++) d0[i] = (d0[i] + d1[i]) + (d2[i] + d3[i]);
                stx1_if(gs + k.y, (d0[0] + d0[1]) + xr.x, (d0[2] + d0[3]) + xr.y, tag, fl & 4u);
            }
            c_out = clk();
            TR(19);
        }
        tagp = tag;
        tag = next_tag(tag);
    }
    if (b0_ == 0 && t0_ == 0) stg_u32(gs + O_EPOCH, ep == 2u ? 0u : ep + 1u);
}

typedef CUresult (*EncodeFn)(CUtensorMap*, CUtensorMapDataType, cuuint32_t, void*, const cuuint64_t*, const cuuint64_t*,
                             const cuuint32_t*, const cuuint32_t*, CUtensorMapInterleave, CUtensorMapSwizzle,
                             CUtensorMapL2promotion, CUtensorMapFloatOOBfill);

void make_map(EncodeFn enc, CUtensorMap* m, const void* p, uint64_t cols, uint64_t rows, uint32_t box_rows) {
    cuuint64_t dims[2] = {cols, rows};
    cuuint64_t strides[1] = {cols * 2};
    cuuint32_t box[2] = {64, box_rows};
    cuuint32_t es[2] = {1, 1};
    enc(m, CU_TENSOR_MAP_DATA_TYPE_BFLOAT16, 2, const_cast<void*>(p), dims, strides, box, es, CU_TENSOR_MAP_INTERLEAVE_NONE,
        CU_TENSOR_MAP_SWIZZLE_128B, CU_TENSOR_MAP_L2_PROMOTION_NONE, CU_TENSOR_MAP_FLOAT_OOB_FILL_NONE);
}

}

extern "C" void kernel_launch(void* const* d_in, const int* in_sizes, int n_in, void* d_out, int out_size) {
    (void)in_sizes; (void)n_in; (void)out_size;
    static EncodeFn enc = nullptr;
    if (!enc) {
        void* fn = nullptr;
        cudaDriverEntryPointQueryResult st;
        cudaGetDriverEntryPoint("cuTensorMapEncodeTiled", &fn, cudaEnableDefault, &st);
        enc = (EncodeFn)fn;
        cudaFuncSetAttribute(fused_decode_kernel, cudaFuncAttributeMaxDynamicSharedMemorySize, SM_TOTAL);
    }
    Maps maps;
    make_map(enc, &maps.k, d_in[1], 128, 8ull * SK, 64);
    make_map(enc, &maps.v, d_in[2], 128, 8ull * SK, 64);
    make_map(enc, &maps.wo, d_in[4], 512, 4096, 64);
    make_map(enc, &maps.w1, d_in[6], 1792, 512, 64);
    make_map(enc, &maps.w3, d_in[7], 1792, 512, 64);
    make_map(enc, &maps.w2, d_in[8], 512, 1792, 56);
    fused_decode_kernel<<<NCTA, NTHREADS, SM_TOTAL>>>(maps, (const __nv_bfloat16*)d_in[0], (const __nv_bfloat16*)d_in[3], (__nv_bfloat16*)d_out);
}
```

```cpp
#include <cuda_runtime.h>
#include <cuda_bf16.h>
#include <cuda.h>
#include <stdint.h>

#define KTRACE 0
#define DEPTH 4
#define TAU 660
#define TOFF 1100
#define T8 6700
#define TAU2 760
#define MAXMODE 1
#define KEEPALIVE 6
#define KA_FROM 6
#define KA_STOP 1
#define DLY_Q 350
#define DLY_A 250
#define DLY_O 250
#define DLY_F1 450
#define DLY_F2 450

namespace {

constexpr int NCTA = 128;
constexpr int NTHREADS = 384;
constexpr int SK = 32768, WIN = 4096;

constexpr int SM_WQ = 0;
constexpr int SM_K = 32768;
constexpr int SM_V = 98304;
constexpr int SM_WO = 163840;
constexpr int SM_W1 = SM_K;
constexpr int SM_W2 = SM_K + 32768;
constexpr int SM_MISC = 196608;
constexpr int SM_XS = SM_MISC;
constexpr int XS_Q = 0, XS_O = 1024, XS_F1 = 2048, XS_F2 = 3072;
constexpr int SM_QS = SM_XS + 4096;
constexpr int SM_PS = SM_QS + 1024;
constexpr int SM_LP = SM_PS + 2048;
constexpr int SM_MW = SM_LP + 1024;
constexpr int SM_XR = SM_MW + 128;
constexpr int SM_XR2 = SM_XR + 512;
constexpr int SM_STOP = SM_XR2 + 256;
constexpr int SM_ONES = SM_STOP + 16;
constexpr int SM_BAR = SM_ONES + 16;
constexpr int MB_K = 0, MB_V = 4, MB_WO = 8, MB_W13 = 10, MB_W2 = 11, MB_KFREE = 12, MB_W13A = 13;
constexpr int SM_TAB = SM_BAR + 128 + 96;
constexpr int SM_CSF = SM_V;
constexpr int SM_DUMMY = SM_TAB + 6 * 4096;
constexpr int SM_TOTAL = SM_DUMMY + 256;
static_assert(SM_TAB % 16 == 0 && SM_TOTAL <= 232448, "smem");
constexpr int NB_INIT = 1, NB_B = 2, NB_BX = 3, NB_P = 4, NB_SVC = 5, NB_LD = 6;

constexpr int O_RECA = 0;
constexpr int O_STQ = 64;
constexpr int O_ML = 96;
constexpr int O_RECB = 128;
constexpr int O_CSB = 256;
constexpr int O_RECD = 384;
constexpr int O_RECC = 512;
constexpr int O_RECE = 1024;
constexpr int O_STF = 1248;
constexpr int O_CSE = 1280;
constexpr int O_FLV = 1504;
constexpr int PB = 1568;
constexpr int O_EPOCH = NCTA * PB;
constexpr int O_END = O_EPOCH + 32;
__device__ __align__(1024) float g_s[O_END];

struct Maps { CUtensorMap k, v, wo, w1, w3, w2; };

__device__ __forceinline__ uint32_t smem_u32(const void* p) { return (uint32_t)__cvta_generic_to_shared(p); }
__device__ __forceinline__ void mbar_init(uint32_t bar, uint32_t cnt) {
    asm volatile("mbarrier.init.shared::cta.b64 [%0], %1;" ::"r"(bar), "r"(cnt) : "memory");
}
__device__ __forceinline__ void mbar_expect_tx(uint32_t bar, uint32_t bytes) {
    asm volatile("mbarrier.arrive.expect_tx.shared::cta.b64 _, [%0], %1;" ::"r"(bar), "r"(bytes) : "memory");
}
__device__ __forceinline__ void mbar_arrive(uint32_t bar) {
    asm volatile("mbarrier.arrive.shared::cta.b64 _, [%0];" ::"r"(bar) : "memory");
}
__device__ __forceinline__ bool mbar_try(uint32_t bar) {
    uint32_t ok;
    asm volatile("{\n.reg .pred p;\nmbarrier.try_wait.parity.shared::cta.b64 p, [%1], 0;\nselp.u32 %0, 1, 0, p;\n}"
                 : "=r"(ok) : "r"(bar) : "memory");
    return ok != 0;
}
__device__ __forceinline__ bool mbar_test(uint32_t bar) {
    uint32_t ok;
    asm volatile("{\n.reg .pred p;\nmbarrier.test_wait.parity.shared::cta.b64 p, [%1], 0;\nselp.u32 %0, 1, 0, p;\n}"
                 : "=r"(ok) : "r"(bar) : "memory");
    return ok != 0;
}
__device__ __forceinline__ void mbar_wait(uint32_t bar) {
    int n = 0;
#pragma unroll 1
    while (!mbar_try(bar) && ++n < (1 << 17)) { }
}
__device__ __forceinline__ void tma2d(uint32_t dst, const CUtensorMap* m, int c0, int c1, uint32_t bar) {
    asm volatile("cp.async.bulk.tensor.2d.shared::cluster.global.mbarrier::complete_tx::bytes [%0], [%1, {%3, %4}], [%2];"
                 ::"r"(dst), "l"((uint64_t)m), "r"(bar), "r"(c0), "r"(c1) : "memory");
}
template <int ID, int N> __device__ __forceinline__ void bar_sync() { asm volatile("bar.sync %0, %1;" ::"n"(ID), "n"(N) : "memory"); }
__device__ __forceinline__ void init_fence() {
    asm volatile("fence.mbarrier_init.release.cluster;" ::: "memory");
    asm volatile("fence.proxy.async.shared::cta;" ::: "memory");
}
__device__ __forceinline__ uint32_t ldg_u32(const void* p) {
    uint32_t v;
    asm volatile("ld.relaxed.gpu.global.u32 %0, [%1];" : "=r"(v) : "l"(p) : "memory");
    return v;
}
__device__ __forceinline__ void stg_u32(void* p, uint32_t v) {
    asm volatile("st.relaxed.gpu.global.u32 [%0], %1;" ::"l"(p), "r"(v) : "memory");
}
__device__ __forceinline__ void ldx(uint4& v, const void* p) {
    asm volatile("{\n.reg .b64 a, b;\nld.relaxed.gpu.global.v2.b64 {a, b}, [%4];\nmov.b64 {%0,%1}, a;\nmov.b64 {%2,%3}, b;\n}"
                 : "=r"(v.x), "=r"(v.y), "=r"(v.z), "=r"(v.w) : "l"(p) : "memory");
}
__device__ __forceinline__ void ldx(uint2& v, const void* p) {
    asm volatile("{\n.reg .b64 a;\nld.relaxed.gpu.global.b64 a, [%2];\nmov.b64 {%0,%1}, a;\n}" : "=r"(v.x), "=r"(v.y) : "l"(p) : "memory");
}
__device__ __forceinline__ uint32_t tagf(float v, uint32_t tag) { return (__float_as_uint(v) & ~3u) | tag; }
__device__ __forceinline__ void stx1(void* p, float a, float b, uint32_t tag) {
    asm volatile("{\n.reg .b64 a;\nmov.b64 a, {%1,%2};\nst.relaxed.gpu.global.b64 [%0], a;\n}"
                 ::"l"(p), "r"(tagf(a, tag)), "r"(__float_as_uint(b)) : "memory");
}
__device__ __forceinline__ void stx1_if(void* p, float a, float b, uint32_t tag, uint32_t q) {
    asm volatile("{\n.reg .pred q;\n.reg .b64 a;\nsetp.ne.u32 q, %3, 0;\nmov.b64 a, {%1,%2};\n@q st.relaxed.gpu.global.b64 [%0], a;\n}"
                 ::"l"(p), "r"(tagf(a, tag)), "r"(__float_as_uint(b)), "r"(q) : "memory");
}
__device__ __forceinline__ void stx2_if(void* p, float a, float b, float c, float d, uint32_t tag, uint32_t q) {
    asm volatile("{\n.reg .pred q;\n.reg .b64 a, b;\nsetp.ne.u32 q, %5, 0;\nmov.b64 a, {%1,%2};\nmov.b64 b, {%3,%4};\n@q st.relaxed.gpu.global.v2.b64 [%0], {a, b};\n}"
                 ::"l"(p), "r"(tagf(a, tag)), "r"(__float_as_uint(b)), "r"(tagf(c, tag)), "r"(__float_as_uint(d)), "r"(q) : "memory");
}
__device__ __forceinline__ void stx2(void* p, float a, float b, float c, float d, uint32_t tag) {
    asm volatile("{\n.reg .b64 a, b;\nmov.b64 a, {%1,%2};\nmov.b64 b, {%3,%4};\nst.relaxed.gpu.global.v2.b64 [%0], {a, b};\n}"
                 ::"l"(p), "r"(tagf(a, tag)), "r"(__float_as_uint(b)), "r"(tagf(c, tag)), "r"(__float_as_uint(d)) : "memory");
}
__device__ __forceinline__ void lds_v4_if(uint4& v, uint32_t a, uint32_t p) {
    asm volatile("{\n.reg .pred q;\nsetp.ne.u32 q, %5, 0;\n@q ld.shared.v4.u32 {%0,%1,%2,%3}, [%4];\n}"
                 : "+r"(v.x), "+r"(v.y), "+r"(v.z), "+r"(v.w) : "r"(a), "r"(p) : "memory");
}
__device__ __forceinline__ uint4 lds_v4(uint32_t a) {
    uint4 v;
    asm volatile("ld.shared.v4.u32 {%0,%1,%2,%3}, [%4];" : "=r"(v.x), "=r"(v.y), "=r"(v.z), "=r"(v.w) : "r"(a) : "memory");
    return v;
}
__device__ __forceinline__ void sts_v4(uint32_t a, uint32_t x, uint32_t y, uint32_t z, uint32_t w) {
    asm volatile("st.shared.v4.u32 [%0], {%1,%2,%3,%4};" ::"r"(a), "r"(x), "r"(y), "r"(z), "r"(w) : "memory");
}
__device__ __forceinline__ void sts_v2(uint32_t a, uint32_t x, uint32_t y) {
    asm volatile("st.shared.v2.u32 [%0], {%1,%2};" ::"r"(a), "r"(x), "r"(y) : "memory");
}
__device__ __forceinline__ float4 lds_f4(uint32_t a) {
    float4 v;
    asm volatile("ld.shared.v4.f32 {%0,%1,%2,%3}, [%4];" : "=f"(v.x), "=f"(v.y), "=f"(v.z), "=f"(v.w) : "r"(a) : "memory");
    return v;
}
__device__ __forceinline__ float2 lds_f2(uint32_t a) {
    float2 v;
    asm volatile("ld.shared.v2.f32 {%0,%1}, [%2];" : "=f"(v.x), "=f"(v.y) : "r"(a) : "memory");
    return v;
}
__device__ __forceinline__ float lds_f(uint32_t a) {
    float v;
    asm volatile("ld.shared.f32 %0, [%1];" : "=f"(v) : "r"(a) : "memory");
    return v;
}
__device__ __forceinline__ void sts_f(uint32_t a, float v) { asm volatile("st.shared.f32 [%0], %1;" ::"r"(a), "f"(v) : "memory"); }
__device__ __forceinline__ void sts_u16(uint32_t a, uint16_t v) { asm volatile("st.shared.u16 [%0], %1;" ::"r"(a), "h"(v) : "memory"); }
__device__ __forceinline__ void ldsm4(uint32_t* r, uint32_t a) {
    asm volatile("ldmatrix.sync.aligned.m8n8.x4.shared.b16 {%0,%1,%2,%3}, [%4];"
                 : "=r"(r[0]), "=r"(r[1]), "=r"(r[2]), "=r"(r[3]) : "r"(a) : "memory");
}
__device__ __forceinline__ void ldsm4t(uint32_t* r, uint32_t a) {
    asm volatile("ldmatrix.sync.aligned.m8n8.x4.trans.shared.b16 {%0,%1,%2,%3}, [%4];"
                 : "=r"(r[0]), "=r"(r[1]), "=r"(r[2]), "=r"(r[3]) : "r"(a) : "memory");
}
template <int N>
__device__ __forceinline__ void ldw(uint32_t (*wf)[4], uint32_t a) {
#pragma unroll
    for (int s = 0; s < N; s++) ldsm4t(wf[s], a + s * 2048);
}
__device__ __forceinline__ void mma16816(float* d, const uint32_t* a, uint32_t b0, uint32_t b1) {
    asm("mma.sync.aligned.m16n8k16.row.col.f32.bf16.bf16.f32 {%0,%1,%2,%3}, {%4,%5,%6,%7}, {%8,%9}, {%0,%1,%2,%3};"
        : "+f"(d[0]), "+f"(d[1]), "+f"(d[2]), "+f"(d[3])
        : "r"(a[0]), "r"(a[1]), "r"(a[2]), "r"(a[3]), "r"(b0), "r"(b1));
}
__device__ __forceinline__ float ex2(float x) { float y; asm("ex2.approx.ftz.f32 %0, %1;" : "=f"(y) : "f"(x)); return y; }
__device__ __forceinline__ float F(uint32_t u) { return __uint_as_float(u); }
__device__ __forceinline__ uint32_t pack_bf16(float lo, float hi) {
    uint32_t r;
    asm("cvt.rn.bf16x2.f32 %0, %1, %2;" : "=r"(r) : "f"(hi), "f"(lo));
    return r;
}
#define POLL_LIMIT (1 << 18)
__device__ __forceinline__ uint32_t clk() { uint32_t c; asm volatile("mov.u32 %0, %%clock;" : "=r"(c)); return c; }
__device__ __forceinline__ void wait_until(uint32_t c0, uint32_t d) { while (clk() - c0 < d) { } }
__device__ __forceinline__ uint32_t bad(const uint4& a, uint32_t tag) { return (a.x ^ tag) | (a.z ^ tag); }
__device__ __forceinline__ uint32_t bad(const uint2& a, uint32_t tag) { return a.x ^ tag; }
template <int N, int S, typename V>
__device__ __forceinline__ void issue(V* v, const float* p) {
#pragma unroll
    for (int i = 0; i < N; i++) ldx(v[i], p + i * S);
}
template <int N, typename V>
__device__ __forceinline__ bool missing(const V* v, uint32_t tag) {
    uint32_t any = 0;
#pragma unroll
    for (int i = 0; i < N; i++) any |= bad(v[i], tag);
    return __any_sync(~0u, (any & 3u) != 0);
}
template <int N>
__device__ __forceinline__ bool missing2(const uint2* a, const uint4* v, uint32_t tag) {
    uint32_t any = 0;
#pragma unroll
    for (int i = 0; i < N; i++) any |= bad(a[i], tag) | bad(v[i], tag);
    return __any_sync(~0u, (any & 3u) != 0);
}
__device__ __forceinline__ bool missing3(const uint2* a, const uint4* v, const uint4* u, uint32_t tag) {
    const uint32_t any = (bad(a[0], tag) | bad(a[1], tag)) | (bad(v[0], tag) | bad(v[1], tag)) | (bad(u[0], tag) | bad(u[1], tag));
    return __any_sync(~0u, (any & 3u) != 0);
}
__device__ __forceinline__ float rcp(float x) { float y; asm("rcp.approx.ftz.f32 %0, %1;" : "=f"(y) : "f"(x)); return y; }
__device__ __forceinline__ float rsq(float x) { float y; asm("rsqrt.approx.ftz.f32 %0, %1;" : "=f"(y) : "f"(x)); return y; }
template <int N, int S>
__device__ __forceinline__ void prewait(const float* p, uint32_t tag) {
    uint2 u[N];
#pragma unroll 1
    for (int n = 0; n < POLL_LIMIT; n++) {
        issue<N, S>(u, p);
        if (!missing<N>(u, tag)) break;
        __nanosleep(20);
    }
}
template <int N, int S, typename V>
__device__ __forceinline__ void fetch(V* v, const float* p, uint32_t tag) {
    int n = 0;
#pragma unroll 1
    do { issue<N, S>(v, p); } while (missing<N>(v, tag) && ++n < POLL_LIMIT);
}
template <int N>
__device__ __forceinline__ float4 sum_v(const uint4* v) {
    if constexpr (N == 1) {
        return make_float4(F(v[0].x), F(v[0].y), F(v[0].z), F(v[0].w));
    } else {
        const float4 a = sum_v<N / 2>(v), b = sum_v<N / 2>(v + N / 2);
        return make_float4(a.x + b.x, a.y + b.y, a.z + b.z, a.w + b.w);
    }
}
__device__ __forceinline__ float4 ar43(float4 v) {
#pragma unroll
    for (int o = 16; o >= 8; o >>= 1) {
        v.x += __shfl_xor_sync(~0u, v.x, o); v.y += __shfl_xor_sync(~0u, v.y, o);
        v.z += __shfl_xor_sync(~0u, v.z, o); v.w += __shfl_xor_sync(~0u, v.w, o);
    }
    return v;
}
__device__ __forceinline__ int map_f(float v) { const int i = __float_as_int(v); return i ^ ((i >> 31) & 0x7fffffff); }
__device__ __forceinline__ float unmap_f(int i) { return __int_as_float(i ^ ((i >> 31) & 0x7fffffff)); }
constexpr float SM_SCALE = 0.08838834764831845f * 1.4426950408889634f;
__device__ __forceinline__ uint32_t next_tag(uint32_t tag) { return tag == 3u ? 1u : tag + 1u; }
__device__ __forceinline__ void sts_chunk(uint32_t a, const float4& v) {
    const uint32_t h0 = pack_bf16(v.x, v.z), h1 = pack_bf16(v.y, v.w);
    sts_v2(a, h0, h1);
    sts_v2(a + 64, pack_bf16(v.x - F(h0 << 16), v.z - F(h0 & 0xffff0000u)), pack_bf16(v.y - F(h1 << 16), v.w - F(h1 & 0xffff0000u)));
}

#define TR(i) do { } while (0)

__global__ void __launch_bounds__(NTHREADS, 1)
fused_decode_kernel(const __nv_bfloat16* __restrict__ wq, float* __restrict__ gs, const __nv_bfloat16* __restrict__ x0,
                    __nv_bfloat16* __restrict__ out, const __grid_constant__ Maps maps) {
    extern __shared__ __align__(1024) unsigned char smem_raw[];
    const uint32_t sb = smem_u32(smem_raw);
    const int b0_ = blockIdx.x, t0_ = threadIdx.x;
    unsigned long long g0 = 0;
    if (t0_ < 256) {
        const int b = b0_, t = t0_;
        const int hq = (b >> 4) * 4 + ((b >> 3) & 1) * 2 + (b & 1);
        const __nv_bfloat16* src = wq + (size_t)(((b >> 1) & 3) * 128 + (t >> 4)) * 4096 + hq * 128 + (t & 15) * 8;
        const uint32_t dst = sb + SM_WQ + ((t >> 3) & 1) * 16384 + (t >> 4) * 128 + (((t & 7) ^ ((t >> 4) & 7)) << 4);
#pragma unroll
        for (int i = 0; i < 8; i++)
            asm volatile("cp.async.cg.shared.global [%0], [%1], 16;" ::"r"(dst + i * 2048), "l"(src + (size_t)i * 16 * 4096) : "memory");
        asm volatile("cp.async.commit_group;" ::: "memory");
        stx2(gs + b * PB + t * 4, 0.f, 0.f, 0.f, 0.f, 0u);
        if (t * 4 + 1024 < PB) stx2(gs + b * PB + 1024 + t * 4, 0.f, 0.f, 0.f, 0.f, 0u);
    } else if (t0_ == 256) {
        asm volatile("mov.u64 %0, %%globaltimer;" : "=l"(g0));
        const int kvrow = (b0_ >> 4) * SK + (SK - WIN) + (b0_ & 15) * 256;
        mbar_init(sb + SM_BAR, 1);
        init_fence();
        mbar_expect_tx(sb + SM_BAR, 16384);
        tma2d(sb + SM_K, &maps.k, 0, kvrow, sb + SM_BAR);
        tma2d(sb + SM_K + 32768, &maps.k, 64, kvrow, sb + SM_BAR);
    }
    __syncwarp();
    const int wg = __shfl_sync(0xffffffffu, t0_ >> 7, 0);
    if (wg == 2) {
        asm volatile("setmaxnreg.dec.sync.aligned.u32 40;");
        const int b = b0_, w = t0_ >> 5, lane = t0_ & 31;
        const uint32_t bars = sb + SM_BAR;
        if (w == 8) {
            const int stag = (b >> 4) * (TAU / 8);
            auto pace = [&](int slot16) {
                const long long tgt = (long long)(slot16 * TAU / 16 + TOFF + stag);
                unsigned long long g;
                do { asm volatile("mov.u64 %0, %%globaltimer;" : "=l"(g)); } while ((long long)(g - g0) < tgt);
            };
            const int kvrow = (b >> 4) * SK + (SK - WIN) + (b & 15) * 256;
            auto kvchunk = [&](int c) {
                const CUtensorMap* m = (c >> 2) ? &maps.v : &maps.k;
                const uint32_t dst = sb + SM_K + (c >> 2) * 65536 + (c & 3) * 8192;
                mbar_expect_tx(bars + 8 * c, 16384);
                tma2d(dst, m, 0, kvrow + (c & 3) * 64, bars + 8 * c);
                tma2d(dst + 32768, m, 64, kvrow + (c & 3) * 64, bars + 8 * c);
            };
            bar_sync<NB_SVC, 128>();
            asm volatile("bar.arrive %0, 384;" ::"n"(NB_INIT) : "memory");
            if (lane == 0) {
#pragma unroll 1
                for (int c = 1; c < 8; c++) {
                    if (c >= DEPTH) mbar_wait(bars + 8 * (c - DEPTH));
                    pace(c * 16);
                    kvchunk(c);
                }
                const unsigned long long g1 = g0 + T8;
                mbar_expect_tx(bars + 8 * MB_WO, 32768);
                mbar_expect_tx(bars + 8 * MB_W13A, 16384);
                mbar_expect_tx(bars + 8 * MB_W13, 16384);
                mbar_expect_tx(bars + 8 * MB_W2, 14336);
#pragma unroll 1
                for (int i = 0; i < 10; i++) {
                    const int ph = i < 4 ? (b >> 2) * (TAU2 / 32) : i < 8 ? (b & 7) * (TAU2 / 8) : (b >> 3) * (TAU2 / 16);
                    unsigned long long g;
                    do { asm volatile("mov.u64 %0, %%globaltimer;" : "=l"(g)); } while ((long long)(g - g1) < (long long)((i & ~1) * (TAU2 / 2) + ph));
                    const int lo = i & 1, hi = (i >> 1) & 1;
                    if (i < 4) {
                        tma2d(sb + SM_WO + lo * 16384 + hi * 8192, &maps.wo, (b & 3) * 128 + lo * 64, (b >> 2) * 128 + hi * 64, bars + 8 * MB_WO);
                    } else if (i < 8) {
                        if (i == 4) mbar_wait(bars + 8 * MB_KFREE);
                        tma2d(sb + SM_W1 + lo * 16384 + hi * 8192, lo ? &maps.w3 : &maps.w1, (b >> 3) * 112 + hi * 64, (b & 7) * 64, bars + 8 * (hi ? MB_W13 : MB_W13A));
                    } else {
                        tma2d(sb + SM_W2 + lo * 7168, &maps.w2, (b & 7) * 64, (b >> 3) * 112 + lo * 56, bars + 8 * MB_W2);
                    }
                }
            }
            return;
        }
        if (lane == 0) {
#pragma unroll 1
            for (int i = 1 + (w - 9); i <= MB_W13A; i += 3) mbar_init(bars + 8 * i, i == MB_KFREE ? 8 : 1);
            init_fence();
        } else if (w == 11 && lane < 6) {
            asm volatile("prefetch.tensormap [%0];" ::"l"((uint64_t)(&maps.k + lane)) : "memory");
        }
        const unsigned ep = ldg_u32(gs + O_EPOCH);
        __syncwarp();
        bar_sync<NB_SVC, 128>();
        bar_sync<NB_INIT, 384>();
        uint32_t tag = (2u * ep) % 3u + 1u;
        if (w == 9) {
            float* const pq = gs + b * PB + O_STQ + (lane & 15) * 2;
            const uint32_t l16 = (lane & 15) * 16;
#pragma unroll 1
            for (int it = 0; it < 2; ++it) {
                {
                    bar_sync<NB_BX, 288>();
                    const float piv = lds_f(sb + SM_XR);
                    const float4 u = lds_f4(sb + SM_XR + l16), v = lds_f4(sb + SM_XR + 256 + l16);
                    const float a0 = u.x - piv, a1 = u.y - piv, a2 = u.z - piv, a3 = u.w - piv;
                    const float a4 = v.x - piv, a5 = v.y - piv, a6 = v.z - piv, a7 = v.w - piv;
                    float s1 = ((a0 + a1) + (a2 + a3)) + ((a4 + a5) + (a6 + a7));
                    float s2 = (fmaf(a0, a0, a1 * a1) + fmaf(a2, a2, a3 * a3)) + (fmaf(a4, a4, a5 * a5) + fmaf(a6, a6, a7 * a7));
#pragma unroll
                    for (int o = 8; o >= 1; o >>= 1) { s1 += __shfl_xor_sync(~0u, s1, o); s2 += __shfl_xor_sync(~0u, s2, o); }
                    stx1_if(pq, fmaf(128.f, piv, s1), fmaxf(fmaf(-s1 * (1.f / 128.f), s1, s2), 0.f), tag, lane < 16);
                }
                {
                    bar_sync<NB_BX, 288>();
                    const float piv = lds_f(sb + SM_XR2);
                    const float4 u = lds_f4(sb + SM_XR2 + (l16 & 127)), v = lds_f4(sb + SM_XR2 + 128 + (l16 & 127));
                    const float a0 = u.x - piv, a1 = u.y - piv, a2 = u.z - piv, a3 = u.w - piv;
                    const float a4 = v.x - piv, a5 = v.y - piv, a6 = v.z - piv, a7 = v.w - piv;
                    float s1 = ((a0 + a1) + (a2 + a3)) + ((a4 + a5) + (a6 + a7));
                    float s2 = (fmaf(a0, a0, a1 * a1) + fmaf(a2, a2, a3 * a3)) + (fmaf(a4, a4, a5 * a5) + fmaf(a6, a6, a7 * a7));
#pragma unroll
                    for (int o = 4; o >= 1; o >>= 1) { s1 += __shfl_xor_sync(~0u, s1, o); s2 += __shfl_xor_sync(~0u, s2, o); }
                    stx1_if(pq + (O_STF - O_STQ), fmaf(64.f, piv, s1), fmaxf(fmaf(-s1 * (1.f / 64.f), s1, s2), 0.f), tag, lane < 16);
                }
                tag = next_tag(tag);
            }
        } else if (w == 10) {
            float d[4] = {0.f, 0.f, 0.f, 0.f};
            bool told = false;
            if (KA_FROM >= 0) mbar_wait(bars + 8 * (KA_FROM >= 0 ? KA_FROM : 0));
#pragma unroll 1
            for (int n = 0; n < 1000; n++) {
                asm volatile("mma.sync.aligned.m16n8k16.row.col.f32.bf16.bf16.f32 {%0,%1,%2,%3}, {%4,%4,%4,%4}, {%4,%4}, {%0,%1,%2,%3};"
                             : "+f"(d[0]), "+f"(d[1]), "+f"(d[2]), "+f"(d[3]) : "r"(0u));
                bool stop = false;
#pragma unroll 1
                for (int j = 0; j < KEEPALIVE && !stop; j++) {
                    if (!told && mbar_test(bars + 8 * (MB_V + 3))) {
                        stx1_if(gs + b * PB + O_FLV + (lane & 15) * 2, 0.f, 0.f, tag, lane < 16);
                        told = true;
                    }
                    stop = lds_f(sb + SM_STOP) != 0.f;
                }
                if (stop) break;
            }
            if (d[0] == 123.456f) sts_f(sb + SM_STOP + 4, d[1]);
        } else {
#pragma unroll 1
            for (int it = 0; it < 2; ++it) {
                bar_sync<NB_P, 288>();
                const float M = unmap_f(__float_as_int(lds_f(sb + SM_MW + it * 16 + (lane & 3) * 4))) * SM_SCALE;
                const float4 l0 = lds_f4(sb + SM_LP + lane * 32), l1 = lds_f4(sb + SM_LP + lane * 32 + 16);
                float l = ((l0.x + l0.y) + (l0.z + l0.w)) + ((l1.x + l1.y) + (l1.z + l1.w));
                l += __shfl_xor_sync(~0u, l, 4);
                l += __shfl_xor_sync(~0u, l, 8);
                l += __shfl_xor_sync(~0u, l, 16);
                if (lane < 16) stx1(gs + b * PB + O_ML + lane * 2, l, M, tag);
                tag = next_tag(tag);
            }
        }
        return;
    }

    asm volatile("setmaxnreg.inc.sync.aligned.u32 232;");
    const uint32_t bars = sb + SM_BAR;
    const unsigned ep = ldg_u32(gs + O_EPOCH);
    {
        const int b = b0_, t = t0_, w = t >> 5, lane = t & 31, g = lane >> 2, c = lane & 3, pl = lane >> 3, ch = lane & 7;
        const int kc = 32 * (w & 3) + (ch >> 2) * 16 + 2 * (ch & 3);
        const __nv_bfloat16* xp = x0 + ((b >> 1) & 3) * 128 + kc;
        const uint32_t x01 = *reinterpret_cast<const uint32_t*>(xp), x89 = *reinterpret_cast<const uint32_t*>(xp + 8);
        const uint32_t lt = ((lane & 7) + ((lane >> 4) & 1) * 8) * 128 + ((((w & 3) * 2 + ((lane >> 3) & 1)) ^ (lane & 7)) << 4);
        const uint32_t o_exp = b * PB + w * 16 + g * 2, o_ld = (w & 3) * 32 + ch * 4;
        const uint32_t a_xs = sb + SM_XS + (w & 3) * 256 + (ch & 3) * 16 + (ch >> 2) * 8;
        const int hA = 2 * (c & 1);
        const uint32_t tb = sb + SM_TAB + t * 16;
        sts_v4(tb, sb + SM_XS + (lane & 15) * 16, a_xs, sb + SM_XR + o_ld * 4,
               (lane < 8 ? 1u : 0u) | (lane < 16 ? 2u : 0u) | (c == 0 ? 4u : 0u) | (c == 1 ? 8u : 0u) | (c < 2 ? 16u : 0u) | ((g & 1) ? 32u : 0u) |
               ((b < 16 && w == ((b >> 3) * 2 + (b & 1)) && pl == 0) ? 64u : 0u) | ((lane >> 4) ? 128u : 0u) | (((lane >> 3) & 1) ? 256u : 0u) | ((c & 1) ? 512u : 0u) | (lane < 4 ? 1024u : 0u) | (w << 16));
        sts_v4(tb + 4096, O_RECA + (pl * 8 + (b & 6) + ((w >> 1) & 1)) * PB + (o_ld & 63), (c == 0 ? O_RECB : O_CSB) + o_exp,
               sb + SM_WQ + (w >> 2) * 16384 + lt, ((b >> 1) & 3) * 128 + kc);
        sts_v4(tb + 2 * 4096, ((b & ~15) + ((w >> 1) & 1) * 8 + (w & 1)) * PB, O_RECC + b * PB + hA * 128 + w * 16 + g * 2,
               sb + SM_QS + ((g >> 1) * 4 + (w & 3)) * 64 + c * 16 + (g & 1) * 8, c < 2 ? sb + SM_PS + w * 256 + (hA * 4 + (g >> 1)) * 16 + (g & 1) * 4 : sb + SM_DUMMY + 4 * g + 128);
        sts_v4(tb + 3 * 4096, c < 2 ? sb + SM_LP + ((w * 4 + hA) * 8 + g) * 4 : sb + SM_DUMMY + 4 * g, sb + SM_MW + c * 4, sb + SM_MW + hA * 4,
                 ((b & ~15) + pl) * PB + O_RECC + ((b >> 2) & 3) * 128 + o_ld);
        sts_v4(tb + 4 * 4096, ((b & ~15) + pl) * PB + O_ML + ((b >> 2) & 3) * 2, O_RECD + (pl * 4 + ((b >> 1) & 3)) * PB + (b & 1) * 64 + (o_ld & 63),
               (c == 0 ? O_RECE : O_CSE) + b * PB + w * 32 + g * 4, sb + SM_W1 + (w >> 2) * 8192 + lt);
        sts_v4(tb + 5 * 4096, ((b & ~7) + pl) * PB + O_RECE + w * 32 + ch * 4, O_RECA + b * PB + (w & 3) * 16 + g * 2,
               sb + SM_XS + XS_F2 + (((w >> 1) * 4 + ((lane >> 3) & 1)) * 4 + (ch >> 1)) * 16 + ((w & 1) * 4 + (lane >> 4) * 2 + (ch & 1)) * 2,
               sb + SM_XR2 + ((w & 3) * 4 + (g >> 1)) * 16 + (g & 1) * 8);
        if (w < 4) sts_v4(sb + SM_XR + o_ld * 4, x01 << 16, x89 << 16, x01 & 0xffff0000u, x89 & 0xffff0000u);
        if (t == 0) sts_f(sb + SM_STOP, 0.f);
        if (t == 0) sts_v4(sb + SM_ONES, 0x3F803F80u, 0x3F803F80u, 0x3F803F80u, 0x3F803F80u);
        if (t < 2) sts_v4(sb + SM_MW + t * 16, 0x80000000u, 0x80000000u, 0x80000000u, 0x80000000u);
    }
    uint32_t kf[2][8][4], vf[16][4];

    bar_sync<NB_INIT, 384>();
    asm volatile("cp.async.wait_group 0;" ::: "memory");
    bar_sync<NB_B, 256>();
    const uint32_t tb = sb + SM_TAB + t0_ * 16;
    const uint4 cm = lds_v4(tb);
    const uint32_t a_bf = cm.x, a_xs = cm.y, a_xr = cm.z, fl = cm.w;
    const uint32_t w = fl >> 16;

    uint32_t tagp = 0;
    uint32_t tag = (2u * ep) % 3u + 1u;
    uint32_t c_out = clk();
#pragma unroll 1
    for (int it = 0; it < 3; ++it) {
        uint32_t wf[8][4];
        uint4 bb[4];
        const uint32_t exp_mask = it == 0 ? 12u : 4u;
        TR(0);
        {
            if (it == 2 && (b0_ >= 16 || w >= 4)) break;
            const uint4 k = lds_v4(tb + 4096);
            if (w < 4) {
                float4 xv;
                if (it > 0) {
                    uint4 v[4];
                    wait_until(c_out, DLY_Q);
                    TR(1);
                    int n = 0;
#pragma unroll 1
                    do {
                        issue<4, 32 * PB>(v, gs + k.x);
                        ldw<8>(wf, k.z);
#pragma unroll
                        for (int i = 0; i < 4; i++) bb[i] = lds_v4(sb + SM_ONES);
                    } while (missing<4>(v, tagp) && ++n < POLL_LIMIT);
                    TR(2);
                    xv = ar43(sum_v<4>(v));
                } else {
                    xv = lds_f4(a_xr);
                    ldw<8>(wf, k.z);
#pragma unroll
                    for (int i = 0; i < 4; i++) bb[i] = lds_v4(sb + SM_ONES);
                }
                sts_chunk(a_xs + XS_Q, xv);
                if (fl & 64u) {
                    *reinterpret_cast<uint32_t*>(out + k.w) = pack_bf16(xv.x, xv.z);
                    *reinterpret_cast<uint32_t*>(out + k.w + 8) = pack_bf16(xv.y, xv.w);
                }
                if (it == 2) break;
                sts_v4(a_xr, __float_as_uint(xv.x), __float_as_uint(xv.y), __float_as_uint(xv.z), __float_as_uint(xv.w));
            } else {
                ldw<8>(wf, k.z);
#pragma unroll
                for (int i = 0; i < 4; i++) bb[i] = lds_v4(sb + SM_ONES);
            }
            bar_sync<NB_BX, 288>();
            float d0[4] = {0.f, 0.f, 0.f, 0.f}, d1[4] = {0.f, 0.f, 0.f, 0.f}, d2[4] = {0.f, 0.f, 0.f, 0.f}, d3[4] = {0.f, 0.f, 0.f, 0.f};
#pragma unroll
            for (int i = 0; i < 4; i++) lds_v4_if(bb[i], a_bf + XS_Q + i * 256, fl & 1u);
            TR(3);
#pragma unroll
            for (int i = 0; i < 4; i += 2) {
                mma16816(d0, wf[2 * i], bb[i].x, bb[i].y);
                mma16816(d1, wf[2 * i + 1], bb[i].z, bb[i].w);
                mma16816(d2, wf[2 * i + 2], bb[i + 1].x, bb[i + 1].y);
                mma16816(d3, wf[2 * i + 3], bb[i + 1].z, bb[i + 1].w);
            }
#pragma unroll
            for (int i = 0; i < 4; i++) d0[i] = (d0[i] + d1[i]) + (d2[i] + d3[i]);
            const float h = (fl & 4u) ? 1.f : 0.f;
            stx1_if(gs + k.y, fmaf(h, d0[1], d0[0]), fmaf(h, d0[3], d0[2]), tag, fl & exp_mask);
            c_out = clk();
            TR(4);
        }
        {
            const uint4 k = lds_v4(tb + 2 * 4096), k2 = lds_v4(tb + 3 * 4096);
            const uint32_t a_mx = k2.y + it * 16, a_mr = k2.z + it * 16;
            if (it == 0) {
                const int lane = t0_ & 31, i8 = lane & 7;
                const int key = (i8 + 8 * (i8 & 1)) ^ ((lane >> 3) & 1);
                mbar_wait(bars + 8 * (MB_K + (w >> 1)));
                mbar_wait(bars + 8 * (MB_K + 2));
#pragma unroll
                for (int T = 0; T < 2; T++) {
                    const uint32_t rowa = sb + SM_K + (w * 32 + T * 16 + key) * 128;
#pragma unroll
                    for (int s = 0; s < 8; s++)
                        ldsm4(kf[T][s], rowa + (s >> 2) * 32768 + ((((s & 3) * 2 + (lane >> 4)) ^ (key & 7)) << 4));
                }
            }
            if (w < 4) {
                const float* pb = gs + k.x;
                const float* pa = pb + O_RECB + (t0_ & 31) * 4;
                const uint32_t a_cq = sb + SM_XS + (t0_ >> 3) * 256 + 128 + (t0_ & 7) * 16;
                uint4 v[4];
                uint2 st[4];
                wait_until(c_out, DLY_A);
                TR(5);
                if (it == 0) {
                    uint4 cv[4];
                    fetch<4, 2 * PB>(cv, pa + (O_CSB - O_RECB), tag);
                    const float4 u = sum_v<4>(cv);
                    sts_v4(a_cq, __float_as_uint(u.x), __float_as_uint(u.y), __float_as_uint(u.z), __float_as_uint(u.w));
                }
                const float4 csq = lds_f4(a_cq);
                float rstd, mr;
                int n = 0;
#pragma unroll 1
                do {
                    issue<4, 2 * PB>(st, pb + O_STQ);
                    issue<4, 2 * PB>(v, pa);
                    const float mean4 = ((F(st[0].x) + F(st[1].x)) + (F(st[2].x) + F(st[3].x))) * 0.25f;
                    const float e0 = F(st[0].x) - mean4, e1 = F(st[1].x) - mean4, e2 = F(st[2].x) - mean4, e3 = F(st[3].x) - mean4;
                    const float m2 = ((F(st[0].y) + F(st[1].y)) + (F(st[2].y) + F(st[3].y))) + ((e0 * e0 + e1 * e1) + (e2 * e2 + e3 * e3)) * (1.f / 128.f);
                    rstd = rsq(m2 * (1.f / 512.f) + 1e-5f);
                    mr = -mean4 * (1.f / 128.f) * rstd;
                } while (missing2<4>(st, v, tag + (rstd < -1.f ? 1u : 0u)) && ++n < POLL_LIMIT);
                TR(6);
                const float4 q = sum_v<4>(v);
                sts_v2(k.z, pack_bf16(fmaf(q.x, rstd, mr * csq.x), fmaf(q.z, rstd, mr * csq.z)), pack_bf16(fmaf(q.y, rstd, mr * csq.y), fmaf(q.w, rstd, mr * csq.w)));
            }
            bar_sync<NB_B, 256>();
            float s00[4] = {0.f, 0.f, 0.f, 0.f}, s01[4] = {0.f, 0.f, 0.f, 0.f}, s10[4] = {0.f, 0.f, 0.f, 0.f}, s11[4] = {0.f, 0.f, 0.f, 0.f};
#pragma unroll
            for (int i = 0; i < 4; i++) lds_v4_if(bb[i], a_bf + (SM_QS - SM_XS) + i * 256, fl & 2u);
            TR(7);
#pragma unroll
            for (int i = 0; i < 4; i++) {
                mma16816(s00, kf[0][2 * i], bb[i].x, bb[i].y);
                mma16816(s10, kf[1][2 * i], bb[i].x, bb[i].y);
                mma16816(s01, kf[0][2 * i + 1], bb[i].z, bb[i].w);
                mma16816(s11, kf[1][2 * i + 1], bb[i].z, bb[i].w);
            }
#pragma unroll
            for (int i = 0; i < 4; i++) { s00[i] += s01[i]; s10[i] += s11[i]; }
            {
                const bool od = fl & 32u;
                const float xA = fmaxf(fmaxf(s00[0], s00[2]), fmaxf(s10[0], s10[2])), xB = fmaxf(fmaxf(s00[1], s00[3]), fmaxf(s10[1], s10[3]));
                float m = fmaxf(od ? xB : xA, __shfl_xor_sync(~0u, od ? xA : xB, 4));
                asm volatile("{\n.reg .pred q;\nsetp.ne.u32 q, %2, 0;\n@q red.shared.max.s32 [%0], %1;\n}"
                             ::"r"(a_mr + (od ? 4u : 0u)), "r"(map_f(m)), "r"(MAXMODE >= 2 ? ((fl & 18u) == 18u ? 1u : 0u) : (fl & 16u)) : "memory");
            }
            bar_sync<NB_B, 256>();
            const float2 mm = lds_f2(a_mr);
            const float mA = unmap_f(__float_as_int(mm.x)) * SM_SCALE, mB = unmap_f(__float_as_int(mm.y)) * SM_SCALE;
            const bool od = fl & 32u;
            const float pA0 = ex2(fmaf(od ? s00[2] : s00[0], SM_SCALE, -mA)), pA1 = ex2(fmaf(od ? s00[0] : s00[2], SM_SCALE, -mA));
            const float pA2 = ex2(fmaf(od ? s10[2] : s10[0], SM_SCALE, -mA)), pA3 = ex2(fmaf(od ? s10[0] : s10[2], SM_SCALE, -mA));
            const float pB0 = ex2(fmaf(od ? s00[3] : s00[1], SM_SCALE, -mB)), pB1 = ex2(fmaf(od ? s00[1] : s00[3], SM_SCALE, -mB));
            const float pB2 = ex2(fmaf(od ? s10[3] : s10[1], SM_SCALE, -mB)), pB3 = ex2(fmaf(od ? s10[1] : s10[3], SM_SCALE, -mB));
            sts_f(k.w, F(pack_bf16(pA0, pA1)));
            sts_f(k.w + 8, F(pack_bf16(pA2, pA3)));
            sts_f(k.w + 64, F(pack_bf16(pB0, pB1)));
            sts_f(k.w + 72, F(pack_bf16(pB2, pB3)));
            sts_f(k2.x, (pA0 + pA1) + (pA2 + pA3));
            sts_f(k2.x + 32, (pB0 + pB1) + (pB2 + pB3));
            if (it == 0) {
                if ((t0_ & 31) == 0) mbar_arrive(bars + 8 * MB_KFREE);
                const uint32_t a0 = lds_v4(tb + 4096).z + (SM_V - SM_WQ) + (w >> 2) * 16384;
#pragma unroll
                for (int hf = 0; hf < 4; hf++) {
                    mbar_wait(bars + 8 * (MB_V + hf));
#pragma unroll
                    for (int s = 0; s < 4; s++) ldsm4t(vf[hf * 4 + s], a0 + (hf * 4 + s) * 2048);
                }
            }
            uint4 bc[4];
#pragma unroll
            for (int i = 0; i < 4; i++) bc[i] = lds_v4(sb + SM_ONES);
            TR(8);
            bar_sync<NB_P, 288>();
            float acc[4][4];
#pragma unroll
            for (int i = 0; i < 4; i++) acc[i][0] = acc[i][1] = acc[i][2] = acc[i][3] = 0.f;
#pragma unroll
            for (int i = 0; i < 4; i++) lds_v4_if(bb[i], a_bf + (SM_PS - SM_XS) + i * 256, fl & 2u);
#pragma unroll
            for (int i = 0; i < 4; i++) lds_v4_if(bc[i], a_bf + (SM_PS - SM_XS) + (4 + i) * 256, fl & 2u);
            TR(9);
#pragma unroll
            for (int i = 0; i < 4; i++) {
                mma16816(acc[(2 * i) & 3], vf[2 * i], bb[i].x, bb[i].y);
                mma16816(acc[(2 * i + 1) & 3], vf[2 * i + 1], bb[i].z, bb[i].w);
            }
#pragma unroll
            for (int i = 0; i < 4; i++) {
                mma16816(acc[(2 * i) & 3], vf[8 + 2 * i], bc[i].x, bc[i].y);
                mma16816(acc[(2 * i + 1) & 3], vf[8 + 2 * i + 1], bc[i].z, bc[i].w);
            }
#pragma unroll
            for (int i = 0; i < 4; i++) acc[0][i] = (acc[0][i] + acc[1][i]) + (acc[2][i] + acc[3][i]);
            stx1_if(gs + k.y, acc[0][0], acc[0][2], tag, fl & 16u);
            stx1_if(gs + k.y + 128, acc[0][1], acc[0][3], tag, fl & 16u);
            c_out = clk();
            TR(10);
        }
        {
            const uint4 k = lds_v4(tb + 4096), k4 = lds_v4(tb + 4 * 4096);
            const uint32_t o_c = lds_v4(tb + 3 * 4096).w;
            bool landed = it != 0;
            if (w < 4) {
                uint4 v[4];
                uint2 ml[4];
                float w0, w1, w2, w3;
                if (it == 0) {
                    if (w == 0) prewait<4, 4 * PB>(gs + k4.x + (O_FLV - O_ML), tag); bar_sync<NB_LD, 128>(); }
                int n = 0;
                landed = __all_sync(~0u, mbar_test(bars + 8 * MB_WO));
#pragma unroll 1
                do {
                    issue<4, 4 * PB>(ml, gs + k4.x);
                    wait_until(c_out, DLY_O);
                    TR(11);
                    issue<4, 4 * PB>(v, gs + o_c);
                    ldw<8>(wf, k.z + (SM_WO - SM_WQ));
                    float M = fmaxf(fmaxf(F(ml[0].y), F(ml[1].y)), fmaxf(F(ml[2].y), F(ml[3].y)));
                    M = fmaxf(M, __shfl_xor_sync(~0u, M, 8));
                    M = fmaxf(M, __shfl_xor_sync(~0u, M, 16));
                    w0 = ex2(F(ml[0].y) - M); w1 = ex2(F(ml[1].y) - M); w2 = ex2(F(ml[2].y) - M); w3 = ex2(F(ml[3].y) - M);
                    float L = fmaf(w0, F(ml[0].x), w1 * F(ml[1].x)) + fmaf(w2, F(ml[2].x), w3 * F(ml[3].x));
                    L += __shfl_xor_sync(~0u, L, 8);
                    L += __shfl_xor_sync(~0u, L, 16);
                    const float inv = rcp(L);
                    w0 *= inv; w1 *= inv; w2 *= inv; w3 *= inv;
                } while (missing2<4>(ml, v, tag + ((w0 + w1) + (w2 + w3) < -1.f ? 1u : 0u)) && ++n < POLL_LIMIT);
                TR(12);
                float4 o;
                o.x = fmaf(w0, F(v[0].x), w1 * F(v[1].x)) + fmaf(w2, F(v[2].x), w3 * F(v[3].x));
                o.y = fmaf(w0, F(v[0].y), w1 * F(v[1].y)) + fmaf(w2, F(v[2].y), w3 * F(v[3].y));
                o.z = fmaf(w0, F(v[0].z), w1 * F(v[1].z)) + fmaf(w2, F(v[2].z), w3 * F(v[3].z));
                o.w = fmaf(w0, F(v[0].w), w1 * F(v[1].w)) + fmaf(w2, F(v[2].w), w3 * F(v[3].w));
                sts_chunk(a_xs + XS_O, ar43(o));
            } else {
                ldw<8>(wf, k.z + (SM_WO - SM_WQ));
            }
            if (!landed) { mbar_wait(bars + 8 * MB_WO); ldw<8>(wf, k.z + (SM_WO - SM_WQ)); }
            bar_sync<NB_B, 256>();
            float d0[4] = {0.f, 0.f, 0.f, 0.f}, d1[4] = {0.f, 0.f, 0.f, 0.f}, d2[4] = {0.f, 0.f, 0.f, 0.f}, d3[4] = {0.f, 0.f, 0.f, 0.f};
#pragma unroll
            for (int i = 0; i < 4; i++) lds_v4_if(bb[i], a_bf + XS_O + i * 256, fl & 1u);
#pragma unroll
            for (int i = 0; i < 4; i += 2) {
                mma16816(d0, wf[2 * i], bb[i].x, bb[i].y);
                mma16816(d1, wf[2 * i + 1], bb[i].z, bb[i].w);
                mma16816(d2, wf[2 * i + 2], bb[i + 1].x, bb[i + 1].y);
                mma16816(d3, wf[2 * i + 3], bb[i + 1].z, bb[i + 1].w);
            }
#pragma unroll
            for (int i = 0; i < 4; i++) d0[i] = (d0[i] + d1[i]) + (d2[i] + d3[i]);
            stx1_if(gs + k.y + (O_RECD - O_RECB), d0[0] + d0[1], d0[2] + d0[3], tag, fl & 4u);
            c_out = clk();
            TR(13);
        }
        {
            const uint4 k = lds_v4(tb + 4 * 4096);
            if (w < 2) {
                float4 xr;
                uint4 v[8];
                wait_until(c_out, DLY_F1);
                if (it == 0) mbar_wait(bars + 8 * MB_W13A);
                TR(14);
                int n = 0;
#pragma unroll 1
                do {
                    issue<8, 16 * PB>(v, gs + k.y);
                    ldw<4>(wf, k.w); ldw<4>(wf + 4, k.w + 16384);
                    bb[0] = lds_v4(sb + SM_ONES);
                    bb[1] = lds_v4(sb + SM_ONES);
                    xr = lds_f4(a_xr + (b0_ & 1) * 256);
                } while (missing<8>(v, tag) && ++n < POLL_LIMIT);
                TR(15);
                float4 x = ar43(sum_v<8>(v));
                x.x += xr.x; x.y += xr.y; x.z += xr.z; x.w += xr.w;
                sts_chunk(a_xs + XS_F1, x);
                sts_v4(a_xr + (SM_XR2 - SM_XR), __float_as_uint(x.x), __float_as_uint(x.y), __float_as_uint(x.z), __float_as_uint(x.w));
            } else {
                ldw<4>(wf, k.w); ldw<4>(wf + 4, k.w + 16384);
                bb[0] = lds_v4(sb + SM_ONES);
                bb[1] = lds_v4(sb + SM_ONES);
            }
            if (it == 0) {
                mbar_wait(bars + 8 * MB_W13A); mbar_wait(bars + 8 * MB_W13);
                ldw<4>(wf, k.w); ldw<4>(wf + 4, k.w + 16384);
            }
            bar_sync<NB_BX, 288>();
            {
                float dg[4] = {0.f, 0.f, 0.f, 0.f}, du[4] = {0.f, 0.f, 0.f, 0.f};
                float dg1[4] = {0.f, 0.f, 0.f, 0.f}, du1[4] = {0.f, 0.f, 0.f, 0.f};
                lds_v4_if(bb[0], a_bf + XS_F1, fl & 1u);
                lds_v4_if(bb[1], a_bf + XS_F1 + 256, fl & 1u);
                mma16816(dg, wf[0], bb[0].x, bb[0].y);
                mma16816(du, wf[4], bb[0].x, bb[0].y);
                mma16816(dg1, wf[1], bb[0].z, bb[0].w);
                mma16816(du1, wf[5], bb[0].z, bb[0].w);
                mma16816(dg, wf[2], bb[1].x, bb[1].y);
                mma16816(du, wf[6], bb[1].x, bb[1].y);
                mma16816(dg1, wf[3], bb[1].z, bb[1].w);
                mma16816(du1, wf[7], bb[1].z, bb[1].w);
                const float h = (fl & 4u) ? 1.f : 0.f;
                const float g0 = fmaf(h, dg[1] + dg1[1], dg[0] + dg1[0]), g1 = fmaf(h, dg[3] + dg1[3], dg[2] + dg1[2]);
                const float u0 = fmaf(h, du[1] + du1[1], du[0] + du1[0]), u1 = fmaf(h, du[3] + du1[3], du[2] + du1[2]);
                stx2_if(gs + k.z, g0, g1, u0, u1, tag, w < 7 ? fl & exp_mask : 0u);
            }
            c_out = clk();
            TR(16);
        }
        {
            const uint4 k = lds_v4(tb + 5 * 4096);
            const uint32_t a0 = lds_v4(tb + 4 * 4096).w + (SM_W2 - SM_W1) - (w >> 2) * 8192;
            if (KA_STOP == 0 && it == 1 && t0_ == 255) sts_f(sb + SM_STOP, 1.f);
            bool landed = it != 0;
            float2 xr = make_float2(0.f, 0.f);
            if (b0_ < 8) xr = lds_f2(k.w);
            if (w < 7) {
                const bool b4 = fl & 128u, b3 = fl & 256u;
                const float* pa = gs + k.x;
                const float* ps = gs + ((b0_ & ~7) + ((t0_ >> 3) & 3)) * PB + O_STF;
                uint4 v[2];
                uint2 st[2];
                wait_until(c_out, DLY_F2);
                TR(17);
                const uint32_t a_cs = sb + SM_CSF + t0_ * 8;
                float2 cs = lds_f2(a_cs);
                uint4 cv[2];
                const float* pc = pa + (it == 0 ? O_CSE - O_RECE : 0);
                int n = 0;
                landed = __all_sync(~0u, mbar_test(bars + 8 * MB_W2));
#pragma unroll 1
                do {
                    issue<2, 4 * PB>(st, ps);
                    issue<2, 4 * PB>(v, pa);
                    if (it == 0) issue<2, 4 * PB>(cv, pc); else { cv[0] = make_uint4(tag, 0u, tag, 0u); cv[1] = cv[0]; }
                    ldw<7>(wf, a0);
                } while (missing3(st, v, cv, tag) && ++n < POLL_LIMIT);
                TR(18);
                if (it == 0) {
                    const float4 u = ar43(sum_v<2>(cv));
                    cs.x = b4 ? u.y : u.x;
                    cs.y = b4 ? u.w : u.z;
                    sts_v2(a_cs, __float_as_uint(cs.x), __float_as_uint(cs.y));
                }
                const float4 u0 = sum_v<2>(v);
                float S = F(st[0].x) + F(st[1].x);
                float T = fmaf(fmaf(F(st[0].x), F(st[0].x), F(st[1].x) * F(st[1].x)), 1.f / 64.f, F(st[0].y) + F(st[1].y));
                float G = (b4 ? u0.y : u0.x) + __shfl_xor_sync(~0u, b4 ? u0.x : u0.y, 16);
                float U = (b4 ? u0.w : u0.z) + __shfl_xor_sync(~0u, b4 ? u0.z : u0.w, 16);
                S += __shfl_xor_sync(~0u, S, 16);
                T += __shfl_xor_sync(~0u, T, 16);
                S += __shfl_xor_sync(~0u, S, 8);
                T += __shfl_xor_sync(~0u, T, 8);
                G += __shfl_xor_sync(~0u, G, 8);
                U += __shfl_xor_sync(~0u, U, 8);
                const float mean = S * (1.f / 512.f);
                const float rstd = rsq(fmaxf(fmaf(-mean, mean, T * (1.f / 512.f)), 0.f) + 1e-5f);
                G = rstd * fmaf(-mean, cs.x, G);
                U = rstd * fmaf(-mean, cs.y, U);
                const float hv = G * rcp(1.f + ex2(-1.4426950408889634f * G)) * U;
                const uint32_t hh = pack_bf16(hv, 0.f), ll = pack_bf16(hv - F(hh << 16), 0.f);
                sts_u16(k.z, (uint16_t)(b3 ? ll : hh));
            } else {
                ldw<7>(wf, a0);
            }
            if (!landed) { mbar_wait(bars + 8 * MB_W2); ldw<7>(wf, a0); }
            bar_sync<NB_B, 256>();
            if (w < 4) {
                float d0[4] = {0.f, 0.f, 0.f, 0.f}, d1[4] = {0.f, 0.f, 0.f, 0.f}, d2[4] = {0.f, 0.f, 0.f, 0.f}, d3[4] = {0.f, 0.f, 0.f, 0.f};
#pragma unroll
                for (int i = 0; i < 4; i++) lds_v4_if(bb[i], a_bf + XS_F2 + i * 256, fl & 1u);
                mma16816(d0, wf[0], bb[0].x, bb[0].y);
                mma16816(d1, wf[1], bb[0].z, bb[0].w);
                mma16816(d2, wf[2], bb[1].x, bb[1].y);
                mma16816(d3, wf[3], bb[1].z, bb[1].w);
                mma16816(d0, wf[4], bb[2].x, bb[2].y);
                mma16816(d1, wf[5], bb[2].z, bb[2].w);
                mma16816(d2, wf[6], bb[3].x, bb[3].y);
#pragma unroll
                for (int i = 0; i < 4; i++) d0[i] = (d0[i] + d1[i]) + (d2[i] + d3[i]);
                stx1_if(gs + k.y, (d0[0] + d0[1]) + xr.x, (d0[2] + d0[3]) + xr.y, tag, fl & 4u);
            }
            if (KA_STOP == 1 && it == 1 && t0_ == 255) sts_f(sb + SM_STOP, 1.f);
            c_out = clk();
            TR(19);
        }
        tagp = tag;
        tag = next_tag(tag);
    }
    if (KA_STOP == 2 && t0_ == 0) sts_f(sb + SM_STOP, 1.f);
    if (b0_ == 0 && t0_ == 0) stg_u32(gs + O_EPOCH, ep == 2u ? 0u : ep + 1u);
}

typedef CUresult (*EncodeFn)(CUtensorMap*, CUtensorMapDataType, cuuint32_t, void*, const cuuint64_t*, const cuuint64_t*,
                             const cuuint32_t*, const cuuint32_t*, CUtensorMapInterleave, CUtensorMapSwizzle,
                             CUtensorMapL2promotion, CUtensorMapFloatOOBfill);

void make_map(EncodeFn enc, CUtensorMap* m, const void* p, uint64_t cols, uint64_t rows, uint32_t box_rows) {
    cuuint64_t dims[2] = {cols, rows};
    cuuint64_t strides[1] = {cols * 2};
    cuuint32_t box[2] = {64, box_rows};
    cuuint32_t es[2] = {1, 1};
    enc(m, CU_TENSOR_MAP_DATA_TYPE_BFLOAT16, 2, const_cast<void*>(p), dims, strides, box, es, CU_TENSOR_MAP_INTERLEAVE_NONE,
        CU_TENSOR_MAP_SWIZZLE_128B, CU_TENSOR_MAP_L2_PROMOTION_NONE, CU_TENSOR_MAP_FLOAT_OOB_FILL_NONE);
}

}

extern "C" void kernel_launch(void* const* d_in, const int* in_sizes, int n_in, void* d_out, int out_size) {
    (void)in_sizes; (void)n_in; (void)out_size;
    static EncodeFn enc = nullptr;
    static float* scratch = nullptr;
    if (!enc) {
        void* fn = nullptr;
        cudaDriverEntryPointQueryResult st;
        cudaGetDriverEntryPoint("cuTensorMapEncodeTiled", &fn, cudaEnableDefault, &st);
        enc = (EncodeFn)fn;
        cudaGetSymbolAddress((void**)&scratch, g_s);
        cudaFuncSetAttribute(fused_decode_kernel, cudaFuncAttributeMaxDynamicSharedMemorySize, SM_TOTAL);
    }
    Maps maps;
    make_map(enc, &maps.k, d_in[1], 128, 8ull * SK, 64);
    make_map(enc, &maps.v, d_in[2], 128, 8ull * SK, 64);
    make_map(enc, &maps.wo, d_in[4], 512, 4096, 64);
    make_map(enc, &maps.w1, d_in[6], 1792, 512, 64);
    make_map(enc, &maps.w3, d_in[7], 1792, 512, 64);
    make_map(enc, &maps.w2, d_in[8], 512, 1792, 56);
    fused_decode_kernel<<<NCTA, NTHREADS, SM_TOTAL>>>((const __nv_bfloat16*)d_in[3], scratch, (const __nv_bfloat16*)d_in[0], (__nv_bfloat16*)d_out, maps);
}
```

```cpp
#include <cuda_runtime.h>
#include <cuda_bf16.h>
#include <cuda.h>
#include <stdint.h>

#define KTRACE 0
#define DEPTH 4
#define TAU 660
#define TOFF 1100
#define T8 6700
#define TAU2 760
#define KEEPALIVE 6
#define DLY_Q 350
#define DLY_A 250
#define DLY_O 250
#define DLY_ML 150
#define DLY_F1 450
#define DLY_F2 450

namespace {

constexpr int NCTA = 128;
constexpr int NTHREADS = 384;
constexpr int SK = 32768, WIN = 4096;

constexpr int SM_WQ = 0;
constexpr int SM_K = 32768;
constexpr int SM_V = 98304;
constexpr int SM_WO = 163840;
constexpr int SM_W1 = SM_K;
constexpr int SM_W2 = SM_K + 32768;
constexpr int SM_MISC = 196608;
constexpr int SM_XS = SM_MISC;
constexpr int XS_Q = 0, XS_O = 1024, XS_F1 = 2048, XS_F2 = 3072;
constexpr int SM_QS = SM_XS + 4096;
constexpr int SM_PS = SM_QS + 1024;
constexpr int SM_LP = SM_PS + 2048;
constexpr int SM_MW = SM_LP + 1024;
constexpr int SM_XR = SM_MW + 128;
constexpr int SM_XR2 = SM_XR + 512;
constexpr int SM_STOP = SM_XR2 + 256;
constexpr int SM_ONES = SM_STOP + 16;
constexpr int SM_BAR = SM_ONES + 16;
constexpr int MB_K = 0, MB_V = 4, MB_WO = 8, MB_W13 = 10, MB_W2 = 11, MB_KFREE = 12, MB_W13A = 13;
constexpr int SM_TAB = SM_BAR + 128 + 96;
constexpr int SM_CSF = SM_V;
constexpr int SM_DUMMY = SM_TAB + 6 * 4096;
constexpr int SM_TOTAL = SM_DUMMY + 256;
static_assert(SM_TAB % 16 == 0 && SM_TOTAL <= 232448, "smem");
constexpr int NB_INIT = 1, NB_B = 2, NB_BX = 3, NB_P = 4, NB_SVC = 5, NB_LD = 6;

constexpr int O_RECA = 0;
constexpr int O_STQ = 64;
constexpr int O_ML = 96;
constexpr int O_RECB = 128;
constexpr int O_CSB = 256;
constexpr int O_RECD = 384;
constexpr int O_RECC = 512;
constexpr int O_RECE = 1024;
constexpr int O_STF = 1248;
constexpr int O_CSE = 1280;
constexpr int O_FLV = 1504;
constexpr int PB = 1568;
constexpr int O_EPOCH = NCTA * PB;
constexpr int O_END = O_EPOCH + 32;
__device__ __align__(1024) float g_s[O_END];

struct Maps { CUtensorMap k, v, wo, w1, w3, w2; };

__device__ __forceinline__ uint32_t smem_u32(const void* p) { return (uint32_t)__cvta_generic_to_shared(p); }
__device__ __forceinline__ void mbar_init(uint32_t bar, uint32_t cnt) {
    asm volatile("mbarrier.init.shared::cta.b64 [%0], %1;" ::"r"(bar), "r"(cnt) : "memory");
}
__device__ __forceinline__ void mbar_expect_tx(uint32_t bar, uint32_t bytes) {
    asm volatile("mbarrier.arrive.expect_tx.shared::cta.b64 _, [%0], %1;" ::"r"(bar), "r"(bytes) : "memory");
}
__device__ __forceinline__ void mbar_arrive(uint32_t bar) {
    asm volatile("mbarrier.arrive.shared::cta.b64 _, [%0];" ::"r"(bar) : "memory");
}
__device__ __forceinline__ bool mbar_try(uint32_t bar) {
    uint32_t ok;
    asm volatile("{\n.reg .pred p;\nmbarrier.try_wait.parity.shared::cta.b64 p, [%1], 0;\nselp.u32 %0, 1, 0, p;\n}"
                 : "=r"(ok) : "r"(bar) : "memory");
    return ok != 0;
}
__device__ __forceinline__ bool mbar_test(uint32_t bar) {
    uint32_t ok;
    asm volatile("{\n.reg .pred p;\nmbarrier.test_wait.parity.shared::cta.b64 p, [%1], 0;\nselp.u32 %0, 1, 0, p;\n}"
                 : "=r"(ok) : "r"(bar) : "memory");
    return ok != 0;
}
__device__ __forceinline__ void mbar_wait(uint32_t bar) {
    int n = 0;
#pragma unroll 1
    while (!mbar_try(bar) && ++n < (1 << 17)) { }
}
__device__ __forceinline__ void tma2d(uint32_t dst, const CUtensorMap* m, int c0, int c1, uint32_t bar) {
    asm volatile("cp.async.bulk.tensor.2d.shared::cluster.global.mbarrier::complete_tx::bytes [%0], [%1, {%3, %4}], [%2];"
                 ::"r"(dst), "l"((uint64_t)m), "r"(bar), "r"(c0), "r"(c1) : "memory");
}
template <int ID, int N> __device__ __forceinline__ void bar_sync() { asm volatile("bar.sync %0, %1;" ::"n"(ID), "n"(N) : "memory"); }
__device__ __forceinline__ void init_fence() {
    asm volatile("fence.mbarrier_init.release.cluster;" ::: "memory");
    asm volatile("fence.proxy.async.shared::cta;" ::: "memory");
}
__device__ __forceinline__ uint32_t ldg_u32(const void* p) {
    uint32_t v;
    asm volatile("ld.relaxed.gpu.global.u32 %0, [%1];" : "=r"(v) : "l"(p) : "memory");
    return v;
}
__device__ __forceinline__ void stg_u32(void* p, uint32_t v) {
    asm volatile("st.relaxed.gpu.global.u32 [%0], %1;" ::"l"(p), "r"(v) : "memory");
}
__device__ __forceinline__ void ldx(uint4& v, const void* p) {
    asm volatile("{\n.reg .b64 a, b;\nld.relaxed.gpu.global.v2.b64 {a, b}, [%4];\nmov.b64 {%0,%1}, a;\nmov.b64 {%2,%3}, b;\n}"
                 : "=r"(v.x), "=r"(v.y), "=r"(v.z), "=r"(v.w) : "l"(p) : "memory");
}
__device__ __forceinline__ void ldx(uint2& v, const void* p) {
    asm volatile("{\n.reg .b64 a;\nld.relaxed.gpu.global.b64 a, [%2];\nmov.b64 {%0,%1}, a;\n}" : "=r"(v.x), "=r"(v.y) : "l"(p) : "memory");
}
__device__ __forceinline__ uint32_t tagf(float v, uint32_t tag) { return (__float_as_uint(v) & ~3u) | tag; }
__device__ __forceinline__ void stx1(void* p, float a, float b, uint32_t tag) {
    asm volatile("{\n.reg .b64 a;\nmov.b64 a, {%1,%2};\nst.relaxed.gpu.global.b64 [%0], a;\n}"
                 ::"l"(p), "r"(tagf(a, tag)), "r"(__float_as_uint(b)) : "memory");
}
__device__ __forceinline__ void stx1_if(void* p, float a, float b, uint32_t tag, uint32_t q) {
    asm volatile("{\n.reg .pred q;\n.reg .b64 a;\nsetp.ne.u32 q, %3, 0;\nmov.b64 a, {%1,%2};\n@q st.relaxed.gpu.global.b64 [%0], a;\n}"
                 ::"l"(p), "r"(tagf(a, tag)), "r"(__float_as_uint(b)), "r"(q) : "memory");
}
__device__ __forceinline__ void stx2_if(void* p, float a, float b, float c, float d, uint32_t tag, uint32_t q) {
    asm volatile("{\n.reg .pred q;\n.reg .b64 a, b;\nsetp.ne.u32 q, %5, 0;\nmov.b64 a, {%1,%2};\nmov.b64 b, {%3,%4};\n@q st.relaxed.gpu.global.v2.b64 [%0], {a, b};\n}"
                 ::"l"(p), "r"(tagf(a, tag)), "r"(__float_as_uint(b)), "r"(tagf(c, tag)), "r"(__float_as_uint(d)), "r"(q) : "memory");
}
__device__ __forceinline__ void stx2(void* p, float a, float b, float c, float d, uint32_t tag) {
    asm volatile("{\n.reg .b64 a, b;\nmov.b64 a, {%1,%2};\nmov.b64 b, {%3,%4};\nst.relaxed.gpu.global.v2.b64 [%0], {a, b};\n}"
                 ::"l"(p), "r"(tagf(a, tag)), "r"(__float_as_uint(b)), "r"(tagf(c, tag)), "r"(__float_as_uint(d)) : "memory");
}
__device__ __forceinline__ void lds_v4_if(uint4& v, uint32_t a, uint32_t p) {
    asm volatile("{\n.reg .pred q;\nsetp.ne.u32 q, %5, 0;\n@q ld.shared.v4.u32 {%0,%1,%2,%3}, [%4];\n}"
                 : "+r"(v.x), "+r"(v.y), "+r"(v.z), "+r"(v.w) : "r"(a), "r"(p) : "memory");
}
__device__ __forceinline__ uint4 lds_v4(uint32_t a) {
    uint4 v;
    asm volatile("ld.shared.v4.u32 {%0,%1,%2,%3}, [%4];" : "=r"(v.x), "=r"(v.y), "=r"(v.z), "=r"(v.w) : "r"(a) : "memory");
    return v;
}
__device__ __forceinline__ void sts_v4(uint32_t a, uint32_t x, uint32_t y, uint32_t z, uint32_t w) {
    asm volatile("st.shared.v4.u32 [%0], {%1,%2,%3,%4};" ::"r"(a), "r"(x), "r"(y), "r"(z), "r"(w) : "memory");
}
__device__ __forceinline__ void sts_v2(uint32_t a, uint32_t x, uint32_t y) {
    asm volatile("st.shared.v2.u32 [%0], {%1,%2};" ::"r"(a), "r"(x), "r"(y) : "memory");
}
__device__ __forceinline__ float4 lds_f4(uint32_t a) {
    float4 v;
    asm volatile("ld.shared.v4.f32 {%0,%1,%2,%3}, [%4];" : "=f"(v.x), "=f"(v.y), "=f"(v.z), "=f"(v.w) : "r"(a) : "memory");
    return v;
}
__device__ __forceinline__ float2 lds_f2(uint32_t a) {
    float2 v;
    asm volatile("ld.shared.v2.f32 {%0,%1}, [%2];" : "=f"(v.x), "=f"(v.y) : "r"(a) : "memory");
    return v;
}
__device__ __forceinline__ float lds_f(uint32_t a) {
    float v;
    asm volatile("ld.shared.f32 %0, [%1];" : "=f"(v) : "r"(a) : "memory");
    return v;
}
__device__ __forceinline__ void sts_f(uint32_t a, float v) { asm volatile("st.shared.f32 [%0], %1;" ::"r"(a), "f"(v) : "memory"); }
__device__ __forceinline__ void sts_u16(uint32_t a, uint16_t v) { asm volatile("st.shared.u16 [%0], %1;" ::"r"(a), "h"(v) : "memory"); }
__device__ __forceinline__ void ldsm4(uint32_t* r, uint32_t a) {
    asm volatile("ldmatrix.sync.aligned.m8n8.x4.shared.b16 {%0,%1,%2,%3}, [%4];"
                 : "=r"(r[0]), "=r"(r[1]), "=r"(r[2]), "=r"(r[3]) : "r"(a) : "memory");
}
__device__ __forceinline__ void ldsm4t(uint32_t* r, uint32_t a) {
    asm volatile("ldmatrix.sync.aligned.m8n8.x4.trans.shared.b16 {%0,%1,%2,%3}, [%4];"
                 : "=r"(r[0]), "=r"(r[1]), "=r"(r[2]), "=r"(r[3]) : "r"(a) : "memory");
}
template <int N>
__device__ __forceinline__ void ldw(uint32_t (*wf)[4], uint32_t a) {
#pragma unroll
    for (int s = 0; s < N; s++) ldsm4t(wf[s], a + s * 2048);
}
__device__ __forceinline__ void mma16816(float* d, const uint32_t* a, uint32_t b0, uint32_t b1) {
    asm("mma.sync.aligned.m16n8k16.row.col.f32.bf16.bf16.f32 {%0,%1,%2,%3}, {%4,%5,%6,%7}, {%8,%9}, {%0,%1,%2,%3};"
        : "+f"(d[0]), "+f"(d[1]), "+f"(d[2]), "+f"(d[3])
        : "r"(a[0]), "r"(a[1]), "r"(a[2]), "r"(a[3]), "r"(b0), "r"(b1));
}
__device__ __forceinline__ float ex2(float x) { float y; asm("ex2.approx.ftz.f32 %0, %1;" : "=f"(y) : "f"(x)); return y; }
__device__ __forceinline__ float F(uint32_t u) { return __uint_as_float(u); }
__device__ __forceinline__ uint32_t pack_bf16(float lo, float hi) {
    uint32_t r;
    asm("cvt.rn.bf16x2.f32 %0, %1, %2;" : "=r"(r) : "f"(hi), "f"(lo));
    return r;
}
#define POLL_LIMIT (1 << 18)
__device__ __forceinline__ uint32_t clk() { uint32_t c; asm volatile("mov.u32 %0, %%clock;" : "=r"(c)); return c; }
__device__ __forceinline__ void wait_until(uint32_t c0, uint32_t d) { while (clk() - c0 < d) { } }
__device__ __forceinline__ uint32_t bad(const uint4& a, uint32_t tag) { return (a.x ^ tag) | (a.z ^ tag); }
__device__ __forceinline__ uint32_t bad(const uint2& a, uint32_t tag) { return a.x ^ tag; }
template <int N, int S, typename V>
__device__ __forceinline__ void issue(V* v, const float* p) {
#pragma unroll
    for (int i = 0; i < N; i++) ldx(v[i], p + i * S);
}
template <int N, typename V>
__device__ __forceinline__ bool missing(const V* v, uint32_t tag) {
    uint32_t any = 0;
#pragma unroll
    for (int i = 0; i < N; i++) any |= bad(v[i], tag);
    return __any_sync(~0u, (any & 3u) != 0);
}
template <int N>
__device__ __forceinline__ bool missing2(const uint2* a, const uint4* v, uint32_t tag) {
    uint32_t any = 0;
#pragma unroll
    for (int i = 0; i < N; i++) any |= bad(a[i], tag) | bad(v[i], tag);
    return __any_sync(~0u, (any & 3u) != 0);
}
__device__ __forceinline__ bool missing3(const uint2* a, const uint4* v, const uint4* u, uint32_t tag) {
    const uint32_t any = (bad(a[0], tag) | bad(a[1], tag)) | (bad(v[0], tag) | bad(v[1], tag)) | (bad(u[0], tag) | bad(u[1], tag));
    return __any_sync(~0u, (any & 3u) != 0);
}
__device__ __forceinline__ float rcp(float x) { float y; asm("rcp.approx.ftz.f32 %0, %1;" : "=f"(y) : "f"(x)); return y; }
__device__ __forceinline__ float rsq(float x) { float y; asm("rsqrt.approx.ftz.f32 %0, %1;" : "=f"(y) : "f"(x)); return y; }
template <int N, int S>
__device__ __forceinline__ void prewait(const float* p, uint32_t tag) {
    uint2 u[N];
#pragma unroll 1
    for (int n = 0; n < POLL_LIMIT; n++) {
        issue<N, S>(u, p);
        if (!missing<N>(u, tag)) break;
        __nanosleep(20);
    }
}
template <int N, int S, typename V>
__device__ __forceinline__ void fetch(V* v, const float* p, uint32_t tag) {
    int n = 0;
#pragma unroll 1
    do { issue<N, S>(v, p); } while (missing<N>(v, tag) && ++n < POLL_LIMIT);
}
template <int N>
__device__ __forceinline__ float4 sum_v(const uint4* v) {
    if constexpr (N == 1) {
        return make_float4(F(v[0].x), F(v[0].y), F(v[0].z), F(v[0].w));
    } else {
        const float4 a = sum_v<N / 2>(v), b = sum_v<N / 2>(v + N / 2);
        return make_float4(a.x + b.x, a.y + b.y, a.z + b.z, a.w + b.w);
    }
}
__device__ __forceinline__ float4 ar43(float4 v) {
#pragma unroll
    for (int o = 16; o >= 8; o >>= 1) {
        v.x += __shfl_xor_sync(~0u, v.x, o); v.y += __shfl_xor_sync(~0u, v.y, o);
        v.z += __shfl_xor_sync(~0u, v.z, o); v.w += __shfl_xor_sync(~0u, v.w, o);
    }
    return v;
}
__device__ __forceinline__ int map_f(float v) { const int i = __float_as_int(v); return i ^ ((i >> 31) & 0x7fffffff); }
__device__ __forceinline__ float unmap_f(int i) { return __int_as_float(i ^ ((i >> 31) & 0x7fffffff)); }
constexpr float SM_SCALE = 0.08838834764831845f * 1.4426950408889634f;
__device__ __forceinline__ uint32_t next_tag(uint32_t tag) { return tag == 3u ? 1u : tag + 1u; }
__device__ __forceinline__ void sts_chunk(uint32_t a, const float4& v) {
    const uint32_t h0 = pack_bf16(v.x, v.z), h1 = pack_bf16(v.y, v.w);
    sts_v2(a, h0, h1);
    sts_v2(a + 64, pack_bf16(v.x - F(h0 << 16), v.z - F(h0 & 0xffff0000u)), pack_bf16(v.y - F(h1 << 16), v.w - F(h1 & 0xffff0000u)));
}

#define TR(i) do { } while (0)

__global__ void __launch_bounds__(NTHREADS, 1)
fused_decode_kernel(const __nv_bfloat16* __restrict__ wq, float* __restrict__ gs, const __nv_bfloat16* __restrict__ x0,
                    __nv_bfloat16* __restrict__ out, const __grid_constant__ Maps maps) {
    extern __shared__ __align__(1024) unsigned char smem_raw[];
    const uint32_t sb = smem_u32(smem_raw);
    const int b0_ = blockIdx.x, t0_ = threadIdx.x;
    unsigned long long g0 = 0;
    if (t0_ < 256) {
        const int b = b0_, t = t0_;
        const int hq = (b >> 4) * 4 + ((b >> 3) & 1) * 2 + (b & 1);
        const __nv_bfloat16* src = wq + (size_t)(((b >> 1) & 3) * 128 + (t >> 4)) * 4096 + hq * 128 + (t & 15) * 8;
        const uint32_t dst = sb + SM_WQ + ((t >> 3) & 1) * 16384 + (t >> 4) * 128 + (((t & 7) ^ ((t >> 4) & 7)) << 4);
#pragma unroll
        for (int i = 0; i < 8; i++)
            asm volatile("cp.async.cg.shared.global [%0], [%1], 16;" ::"r"(dst + i * 2048), "l"(src + (size_t)i * 16 * 4096) : "memory");
        asm volatile("cp.async.commit_group;" ::: "memory");
        stx2(gs + b * PB + t * 4, 0.f, 0.f, 0.f, 0.f, 0u);
        if (t * 4 + 1024 < PB) stx2(gs + b * PB + 1024 + t * 4, 0.f, 0.f, 0.f, 0.f, 0u);
    } else if (t0_ == 256) {
        asm volatile("mov.u64 %0, %%globaltimer;" : "=l"(g0));
        const int kvrow = (b0_ >> 4) * SK + (SK - WIN) + (b0_ & 15) * 256;
        mbar_init(sb + SM_BAR, 1);
        init_fence();
        mbar_expect_tx(sb + SM_BAR, 16384);
        tma2d(sb + SM_K, &maps.k, 0, kvrow, sb + SM_BAR);
        tma2d(sb + SM_K + 32768, &maps.k, 64, kvrow, sb + SM_BAR);
    }
    __syncwarp();
    const int wg = __shfl_sync(0xffffffffu, t0_ >> 7, 0);
    if (wg == 2) {
        asm volatile("setmaxnreg.dec.sync.aligned.u32 40;");
        const int b = b0_, w = t0_ >> 5, lane = t0_ & 31;
        const uint32_t bars = sb + SM_BAR;
        if (w == 8) {
            const int stag = (b >> 4) * (TAU / 8);
            auto pace = [&](int slot16) {
                const long long tgt = (long long)(slot16 * TAU / 16 + TOFF + stag);
                unsigned long long g;
                do { asm volatile("mov.u64 %0, %%globaltimer;" : "=l"(g)); } while ((long long)(g - g0) < tgt);
            };
            const int kvrow = (b >> 4) * SK + (SK - WIN) + (b & 15) * 256;
            auto kvchunk = [&](int c) {
                const CUtensorMap* m = (c >> 2) ? &maps.v : &maps.k;
                const uint32_t dst = sb + SM_K + (c >> 2) * 65536 + (c & 3) * 8192;
                mbar_expect_tx(bars + 8 * c, 16384);
                tma2d(dst, m, 0, kvrow + (c & 3) * 64, bars + 8 * c);
                tma2d(dst + 32768, m, 64, kvrow + (c & 3) * 64, bars + 8 * c);
            };
            bar_sync<NB_SVC, 128>();
            asm volatile("bar.arrive %0, 384;" ::"n"(NB_INIT) : "memory");
            if (lane == 0) {
#pragma unroll 1
                for (int c = 1; c < 8; c++) {
                    if (c >= DEPTH) mbar_wait(bars + 8 * (c - DEPTH));
                    pace(c * 16);
                    kvchunk(c);
                }
                const unsigned long long g1 = g0 + T8;
                mbar_expect_tx(bars + 8 * MB_WO, 32768);
                mbar_expect_tx(bars + 8 * MB_W13A, 16384);
                mbar_expect_tx(bars + 8 * MB_W13, 16384);
                mbar_expect_tx(bars + 8 * MB_W2, 14336);
#pragma unroll 1
                for (int i = 0; i < 10; i++) {
                    const int ph = i < 4 ? (b >> 2) * (TAU2 / 32) : i < 8 ? (b & 7) * (TAU2 / 8) : (b >> 3) * (TAU2 / 16);
                    unsigned long long g;
                    do { asm volatile("mov.u64 %0, %%globaltimer;" : "=l"(g)); } while ((long long)(g - g1) < (long long)((i & ~1) * (TAU2 / 2) + ph));
                    const int lo = i & 1, hi = (i >> 1) & 1;
                    if (i < 4) {
                        tma2d(sb + SM_WO + lo * 16384 + hi * 8192, &maps.wo, (b & 3) * 128 + lo * 64, (b >> 2) * 128 + hi * 64, bars + 8 * MB_WO);
                    } else if (i < 8) {
                        if (i == 4) mbar_wait(bars + 8 * MB_KFREE);
                        tma2d(sb + SM_W1 + lo * 16384 + hi * 8192, lo ? &maps.w3 : &maps.w1, (b >> 3) * 112 + hi * 64, (b & 7) * 64, bars + 8 * (hi ? MB_W13 : MB_W13A));
                    } else {
                        tma2d(sb + SM_W2 + lo * 7168, &maps.w2, (b & 7) * 64, (b >> 3) * 112 + lo * 56, bars + 8 * MB_W2);
                    }
                }
            }
            return;
        }
        if (lane == 0) {
#pragma unroll 1
            for (int i = 1 + (w - 9); i <= MB_W13A; i += 3) mbar_init(bars + 8 * i, i == MB_KFREE ? 8 : 1);
            init_fence();
        } else if (w == 11 && lane < 6) {
            asm volatile("prefetch.tensormap [%0];" ::"l"((uint64_t)(&maps.k + lane)) : "memory");
        }
        const unsigned ep = ldg_u32(gs + O_EPOCH);
        __syncwarp();
        bar_sync<NB_SVC, 128>();
        bar_sync<NB_INIT, 384>();
        uint32_t tag = (2u * ep) % 3u + 1u;
        if (w == 9) {
            float* const pq = gs + b * PB + O_STQ + (lane & 15) * 2;
            const uint32_t l16 = (lane & 15) * 16;
#pragma unroll 1
            for (int it = 0; it < 2; ++it) {
                {
                    bar_sync<NB_BX, 288>();
                    const float piv = lds_f(sb + SM_XR);
                    const float4 u = lds_f4(sb + SM_XR + l16), v = lds_f4(sb + SM_XR + 256 + l16);
                    const float a0 = u.x - piv, a1 = u.y - piv, a2 = u.z - piv, a3 = u.w - piv;
                    const float a4 = v.x - piv, a5 = v.y - piv, a6 = v.z - piv, a7 = v.w - piv;
                    float s1 = ((a0 + a1) + (a2 + a3)) + ((a4 + a5) + (a6 + a7));
                    float s2 = (fmaf(a0, a0, a1 * a1) + fmaf(a2, a2, a3 * a3)) + (fmaf(a4, a4, a5 * a5) + fmaf(a6, a6, a7 * a7));
#pragma unroll
                    for (int o = 8; o >= 1; o >>= 1) { s1 += __shfl_xor_sync(~0u, s1, o); s2 += __shfl_xor_sync(~0u, s2, o); }
                    stx1_if(pq, fmaf(128.f, piv, s1), fmaxf(fmaf(-s1 * (1.f / 128.f), s1, s2), 0.f), tag, lane < 16);
                }
                {
                    bar_sync<NB_BX, 288>();
                    const float piv = lds_f(sb + SM_XR2);
                    const float4 u = lds_f4(sb + SM_XR2 + (l16 & 127)), v = lds_f4(sb + SM_XR2 + 128 + (l16 & 127));
                    const float a0 = u.x - piv, a1 = u.y - piv, a2 = u.z - piv, a3 = u.w - piv;
                    const float a4 = v.x - piv, a5 = v.y - piv, a6 = v.z - piv, a7 = v.w - piv;
                    float s1 = ((a0 + a1) + (a2 + a3)) + ((a4 + a5) + (a6 + a7));
                    float s2 = (fmaf(a0, a0, a1 * a1) + fmaf(a2, a2, a3 * a3)) + (fmaf(a4, a4, a5 * a5) + fmaf(a6, a6, a7 * a7));
#pragma unroll
                    for (int o = 4; o >= 1; o >>= 1) { s1 += __shfl_xor_sync(~0u, s1, o); s2 += __shfl_xor_sync(~0u, s2, o); }
                    stx1_if(pq + (O_STF - O_STQ), fmaf(64.f, piv, s1), fmaxf(fmaf(-s1 * (1.f / 64.f), s1, s2), 0.f), tag, lane < 16);
                }
                tag = next_tag(tag);
            }
        } else if (w == 10) {
            float d[4] = {0.f, 0.f, 0.f, 0.f};
            bool told = false;
            mbar_wait(bars + 8 * (MB_V + 2));
#pragma unroll 1
            for (int n = 0; n < 1000; n++) {
                asm volatile("mma.sync.aligned.m16n8k16.row.col.f32.bf16.bf16.f32 {%0,%1,%2,%3}, {%4,%4,%4,%4}, {%4,%4}, {%0,%1,%2,%3};"
                             : "+f"(d[0]), "+f"(d[1]), "+f"(d[2]), "+f"(d[3]) : "r"(0u));
                bool stop = false;
#pragma unroll 1
                for (int j = 0; j < KEEPALIVE && !stop; j++) {
                    if (!told && mbar_test(bars + 8 * (MB_V + 3))) {
                        stx1_if(gs + b * PB + O_FLV + (lane & 15) * 2, 0.f, 0.f, tag, lane < 16);
                        told = true;
                    }
                    stop = lds_f(sb + SM_STOP) != 0.f;
                }
                if (stop) break;
            }
            if (d[0] == 123.456f) sts_f(sb + SM_STOP + 4, d[1]);
        } else {
#pragma unroll 1
            for (int it = 0; it < 2; ++it) {
                bar_sync<NB_P, 288>();
                const float M = unmap_f(__float_as_int(lds_f(sb + SM_MW + it * 16 + (lane & 3) * 4))) * SM_SCALE;
                const float4 l0 = lds_f4(sb + SM_LP + lane * 32), l1 = lds_f4(sb + SM_LP + lane * 32 + 16);
                float l = ((l0.x + l0.y) + (l0.z + l0.w)) + ((l1.x + l1.y) + (l1.z + l1.w));
                l += __shfl_xor_sync(~0u, l, 4);
                l += __shfl_xor_sync(~0u, l, 8);
                l += __shfl_xor_sync(~0u, l, 16);
                if (lane < 16) stx1(gs + b * PB + O_ML + lane * 2, l, M, tag);
                tag = next_tag(tag);
            }
        }
        return;
    }

    asm volatile("setmaxnreg.inc.sync.aligned.u32 232;");
    const uint32_t bars = sb + SM_BAR;
    const unsigned ep = ldg_u32(gs + O_EPOCH);
    {
        const int b = b0_, t = t0_, w = t >> 5, lane = t & 31, g = lane >> 2, c = lane & 3, pl = lane >> 3, ch = lane & 7;
        const int kc = 32 * (w & 3) + (ch >> 2) * 16 + 2 * (ch & 3);
        const __nv_bfloat16* xp = x0 + ((b >> 1) & 3) * 128 + kc;
        const uint32_t x01 = *reinterpret_cast<const uint32_t*>(xp), x89 = *reinterpret_cast<const uint32_t*>(xp + 8);
        const uint32_t lt = ((lane & 7) + ((lane >> 4) & 1) * 8) * 128 + ((((w & 3) * 2 + ((lane >> 3) & 1)) ^ (lane & 7)) << 4);
        const uint32_t o_exp = b * PB + w * 16 + g * 2, o_ld = (w & 3) * 32 + ch * 4;
        const uint32_t a_xs = sb + SM_XS + (w & 3) * 256 + (ch & 3) * 16 + (ch >> 2) * 8;
        const int hA = 2 * (c & 1);
        const uint32_t tb = sb + SM_TAB + t * 16;
        sts_v4(tb, sb + SM_XS + (lane & 15) * 16, a_xs, sb + SM_XR + o_ld * 4,
               (lane < 8 ? 1u : 0u) | (lane < 16 ? 2u : 0u) | (c == 0 ? 4u : 0u) | (c == 1 ? 8u : 0u) | (c < 2 ? 16u : 0u) | ((g & 1) ? 32u : 0u) |
               ((b < 16 && w == ((b >> 3) * 2 + (b & 1)) && pl == 0) ? 64u : 0u) | ((lane >> 4) ? 128u : 0u) | (((lane >> 3) & 1) ? 256u : 0u) | ((c & 1) ? 512u : 0u) | (lane < 4 ? 1024u : 0u) | (w << 16));
        sts_v4(tb + 4096, O_RECA + (pl * 8 + (b & 6) + ((w >> 1) & 1)) * PB + (o_ld & 63), (c == 0 ? O_RECB : O_CSB) + o_exp,
               sb + SM_WQ + (w >> 2) * 16384 + lt, ((b >> 1) & 3) * 128 + kc);
        sts_v4(tb + 2 * 4096, ((b & ~15) + ((w >> 1) & 1) * 8 + (w & 1)) * PB, O_RECC + b * PB + hA * 128 + w * 16 + g * 2,
               sb + SM_QS + ((g >> 1) * 4 + (w & 3)) * 64 + c * 16 + (g & 1) * 8, c < 2 ? sb + SM_PS + w * 256 + (hA * 4 + (g >> 1)) * 16 + (g & 1) * 4 : sb + SM_DUMMY + 4 * g + 128);
        sts_v4(tb + 3 * 4096, c < 2 ? sb + SM_LP + ((w * 4 + hA) * 8 + g) * 4 : sb + SM_DUMMY + 4 * g, sb + SM_MW + c * 4, sb + SM_MW + hA * 4,
                 ((b & ~15) + pl) * PB + O_RECC + ((b >> 2) & 3) * 128 + o_ld);
        sts_v4(tb + 4 * 4096, ((b & ~15) + pl) * PB + O_ML + ((b >> 2) & 3) * 2, O_RECD + (pl * 4 + ((b >> 1) & 3)) * PB + (b & 1) * 64 + (o_ld & 63),
               (c == 0 ? O_RECE : O_CSE) + b * PB + w * 32 + g * 4, sb + SM_W1 + (w >> 2) * 8192 + lt);
        sts_v4(tb + 5 * 4096, ((b & ~7) + pl) * PB + O_RECE + w * 32 + ch * 4, O_RECA + b * PB + (w & 3) * 16 + g * 2,
               sb + SM_XS + XS_F2 + (((w >> 1) * 4 + ((lane >> 3) & 1)) * 4 + (ch >> 1)) * 16 + ((w & 1) * 4 + (lane >> 4) * 2 + (ch & 1)) * 2,
               sb + SM_XR2 + ((w & 3) * 4 + (g >> 1)) * 16 + (g & 1) * 8);
        if (w < 4) sts_v4(sb + SM_XR + o_ld * 4, x01 << 16, x89 << 16, x01 & 0xffff0000u, x89 & 0xffff0000u);
        if (t == 0) sts_f(sb + SM_STOP, 0.f);
        if (t == 0) sts_v4(sb + SM_ONES, 0x3F803F80u, 0x3F803F80u, 0x3F803F80u, 0x3F803F80u);
        if (t < 2) sts_v4(sb + SM_MW + t * 16, 0x80000000u, 0x80000000u, 0x80000000u, 0x80000000u);
    }
    uint32_t kf[2][8][4], vf[16][4];

    bar_sync<NB_INIT, 384>();
    asm volatile("cp.async.wait_group 0;" ::: "memory");
    bar_sync<NB_B, 256>();
    const uint32_t tb = sb + SM_TAB + t0_ * 16;
    const uint4 cm = lds_v4(tb);
    const uint32_t a_bf = cm.x, a_xs = cm.y, a_xr = cm.z, fl = cm.w;
    const uint32_t w = fl >> 16;

    uint32_t tagp = 0;
    uint32_t tag = (2u * ep) % 3u + 1u;
    uint32_t c_out = clk();
#pragma unroll 1
    for (int it = 0; it < 3; ++it) {
        uint32_t wf[8][4];
        uint4 bb[4];
        const uint32_t exp_mask = it == 0 ? 12u : 4u;
        TR(0);
        {
            if (it == 2 && (b0_ >= 16 || w >= 4)) break;
            const uint4 k = lds_v4(tb + 4096);
            if (w < 4) {
                float4 xv;
                if (it > 0) {
                    uint4 v[4];
                    wait_until(c_out, DLY_Q);
                    TR(1);
                    int n = 0;
#pragma unroll 1
                    do {
                        issue<4, 32 * PB>(v, gs + k.x);
                        ldw<8>(wf, k.z);
#pragma unroll
                        for (int i = 0; i < 4; i++) bb[i] = lds_v4(sb + SM_ONES);
                    } while (missing<4>(v, tagp) && ++n < POLL_LIMIT);
                    TR(2);
                    xv = ar43(sum_v<4>(v));
                } else {
                    xv = lds_f4(a_xr);
                    ldw<8>(wf, k.z);
#pragma unroll
                    for (int i = 0; i < 4; i++) bb[i] = lds_v4(sb + SM_ONES);
                }
                sts_chunk(a_xs + XS_Q, xv);
                if (fl & 64u) {
                    *reinterpret_cast<uint32_t*>(out + k.w) = pack_bf16(xv.x, xv.z);
                    *reinterpret_cast<uint32_t*>(out + k.w + 8) = pack_bf16(xv.y, xv.w);
                }
                if (it == 2) break;
                sts_v4(a_xr, __float_as_uint(xv.x), __float_as_uint(xv.y), __float_as_uint(xv.z), __float_as_uint(xv.w));
            } else {
                ldw<8>(wf, k.z);
#pragma unroll
                for (int i = 0; i < 4; i++) bb[i] = lds_v4(sb + SM_ONES);
            }
            bar_sync<NB_BX, 288>();
            float d0[4] = {0.f, 0.f, 0.f, 0.f}, d1[4] = {0.f, 0.f, 0.f, 0.f}, d2[4] = {0.f, 0.f, 0.f, 0.f}, d3[4] = {0.f, 0.f, 0.f, 0.f};
#pragma unroll
            for (int i = 0; i < 4; i++) lds_v4_if(bb[i], a_bf + XS_Q + i * 256, fl & 1u);
            TR(3);
#pragma unroll
            for (int i = 0; i < 4; i += 2) {
                mma16816(d0, wf[2 * i], bb[i].x, bb[i].y);
                mma16816(d1, wf[2 * i + 1], bb[i].z, bb[i].w);
                mma16816(d2, wf[2 * i + 2], bb[i + 1].x, bb[i + 1].y);
                mma16816(d3, wf[2 * i + 3], bb[i + 1].z, bb[i + 1].w);
            }
#pragma unroll
            for (int i = 0; i < 4; i++) d0[i] = (d0[i] + d1[i]) + (d2[i] + d3[i]);
            const float h = (fl & 4u) ? 1.f : 0.f;
            stx1_if(gs + k.y, fmaf(h, d0[1], d0[0]), fmaf(h, d0[3], d0[2]), tag, fl & exp_mask);
            c_out = clk();
            TR(4);
        }
        {
            const uint4 k = lds_v4(tb + 2 * 4096), k2 = lds_v4(tb + 3 * 4096);
            const uint32_t a_mr = k2.z + it * 16;
            if (it == 0) {
                const int lane = t0_ & 31, i8 = lane & 7;
                const int key = (i8 + 8 * (i8 & 1)) ^ ((lane >> 3) & 1);
                mbar_wait(bars + 8 * (MB_K + (w >> 1)));
                mbar_wait(bars + 8 * (MB_K + 2));
#pragma unroll
                for (int T = 0; T < 2; T++) {
                    const uint32_t rowa = sb + SM_K + (w * 32 + T * 16 + key) * 128;
#pragma unroll
                    for (int s = 0; s < 8; s++)
                        ldsm4(kf[T][s], rowa + (s >> 2) * 32768 + ((((s & 3) * 2 + (lane >> 4)) ^ (key & 7)) << 4));
                }
            }
            if (w < 4) {
                const float* pb = gs + k.x;
                const float* pa = pb + O_RECB + (t0_ & 31) * 4;
                const uint32_t a_cq = sb + SM_XS + (t0_ >> 3) * 256 + 128 + (t0_ & 7) * 16;
                uint4 v[4];
                uint2 st[4];
                wait_until(c_out, DLY_A);
                TR(5);
                if (it == 0) {
                    uint4 cv[4];
                    fetch<4, 2 * PB>(cv, pa + (O_CSB - O_RECB), tag);
                    const float4 u = sum_v<4>(cv);
                    sts_v4(a_cq, __float_as_uint(u.x), __float_as_uint(u.y), __float_as_uint(u.z), __float_as_uint(u.w));
                }
                const float4 csq = lds_f4(a_cq);
                float rstd, mr;
                int n = 0;
#pragma unroll 1
                do {
                    issue<4, 2 * PB>(st, pb + O_STQ);
                    issue<4, 2 * PB>(v, pa);
                    const float mean4 = ((F(st[0].x) + F(st[1].x)) + (F(st[2].x) + F(st[3].x))) * 0.25f;
                    const float e0 = F(st[0].x) - mean4, e1 = F(st[1].x) - mean4, e2 = F(st[2].x) - mean4, e3 = F(st[3].x) - mean4;
                    const float m2 = ((F(st[0].y) + F(st[1].y)) + (F(st[2].y) + F(st[3].y))) + ((e0 * e0 + e1 * e1) + (e2 * e2 + e3 * e3)) * (1.f / 128.f);
                    rstd = rsq(m2 * (1.f / 512.f) + 1e-5f);
                    mr = -mean4 * (1.f / 128.f) * rstd;
                } while (missing2<4>(st, v, tag + (rstd < -1.f ? 1u : 0u)) && ++n < POLL_LIMIT);
                TR(6);
                const float4 q = sum_v<4>(v);
                sts_v2(k.z, pack_bf16(fmaf(q.x, rstd, mr * csq.x), fmaf(q.z, rstd, mr * csq.z)), pack_bf16(fmaf(q.y, rstd, mr * csq.y), fmaf(q.w, rstd, mr * csq.w)));
            }
            bar_sync<NB_B, 256>();
            float s00[4] = {0.f, 0.f, 0.f, 0.f}, s01[4] = {0.f, 0.f, 0.f, 0.f}, s10[4] = {0.f, 0.f, 0.f, 0.f}, s11[4] = {0.f, 0.f, 0.f, 0.f};
#pragma unroll
            for (int i = 0; i < 4; i++) lds_v4_if(bb[i], a_bf + (SM_QS - SM_XS) + i * 256, fl & 2u);
            TR(7);
#pragma unroll
            for (int i = 0; i < 4; i++) {
                mma16816(s00, kf[0][2 * i], bb[i].x, bb[i].y);
                mma16816(s10, kf[1][2 * i], bb[i].x, bb[i].y);
                mma16816(s01, kf[0][2 * i + 1], bb[i].z, bb[i].w);
                mma16816(s11, kf[1][2 * i + 1], bb[i].z, bb[i].w);
            }
#pragma unroll
            for (int i = 0; i < 4; i++) { s00[i] += s01[i]; s10[i] += s11[i]; }
            {
                const bool od = fl & 32u;
                const float xA = fmaxf(fmaxf(s00[0], s00[2]), fmaxf(s10[0], s10[2])), xB = fmaxf(fmaxf(s00[1], s00[3]), fmaxf(s10[1], s10[3]));
                const float m = fmaxf(od ? xB : xA, __shfl_xor_sync(~0u, od ? xA : xB, 4));
                asm volatile("{\n.reg .pred q;\nsetp.ne.u32 q, %2, 0;\n@q red.shared.max.s32 [%0], %1;\n}"
                             ::"r"(a_mr + (od ? 4u : 0u)), "r"(map_f(m)), "r"(fl & 16u) : "memory");
            }
            bar_sync<NB_B, 256>();
            const float2 mm = lds_f2(a_mr);
            const float mA = unmap_f(__float_as_int(mm.x)) * SM_SCALE, mB = unmap_f(__float_as_int(mm.y)) * SM_SCALE;
            const bool od = fl & 32u;
            const float pA0 = ex2(fmaf(od ? s00[2] : s00[0], SM_SCALE, -mA)), pA1 = ex2(fmaf(od ? s00[0] : s00[2], SM_SCALE, -mA));
            const float pA2 = ex2(fmaf(od ? s10[2] : s10[0], SM_SCALE, -mA)), pA3 = ex2(fmaf(od ? s10[0] : s10[2], SM_SCALE, -mA));
            const float pB0 = ex2(fmaf(od ? s00[3] : s00[1], SM_SCALE, -mB)), pB1 = ex2(fmaf(od ? s00[1] : s00[3], SM_SCALE, -mB));
            const float pB2 = ex2(fmaf(od ? s10[3] : s10[1], SM_SCALE, -mB)), pB3 = ex2(fmaf(od ? s10[1] : s10[3], SM_SCALE, -mB));
            sts_f(k.w, F(pack_bf16(pA0, pA1)));
            sts_f(k.w + 8, F(pack_bf16(pA2, pA3)));
            sts_f(k.w + 64, F(pack_bf16(pB0, pB1)));
            sts_f(k.w + 72, F(pack_bf16(pB2, pB3)));
            sts_f(k2.x, (pA0 + pA1) + (pA2 + pA3));
            sts_f(k2.x + 32, (pB0 + pB1) + (pB2 + pB3));
            if (it == 0) {
                if ((t0_ & 31) == 0) mbar_arrive(bars + 8 * MB_KFREE);
                const uint32_t a0 = lds_v4(tb + 4096).z + (SM_V - SM_WQ) + (w >> 2) * 16384;
#pragma unroll
                for (int hf = 0; hf < 4; hf++) {
                    mbar_wait(bars + 8 * (MB_V + hf));
#pragma unroll
                    for (int s = 0; s < 4; s++) ldsm4t(vf[hf * 4 + s], a0 + (hf * 4 + s) * 2048);
                }
            }
            uint4 bc[4];
#pragma unroll
            for (int i = 0; i < 4; i++) bc[i] = lds_v4(sb + SM_ONES);
            TR(8);
            bar_sync<NB_P, 288>();
            float acc[4][4];
#pragma unroll
            for (int i = 0; i < 4; i++) acc[i][0] = acc[i][1] = acc[i][2] = acc[i][3] = 0.f;
#pragma unroll
            for (int i = 0; i < 4; i++) lds_v4_if(bb[i], a_bf + (SM_PS - SM_XS) + i * 256, fl & 2u);
#pragma unroll
            for (int i = 0; i < 4; i++) lds_v4_if(bc[i], a_bf + (SM_PS - SM_XS) + (4 + i) * 256, fl & 2u);
            TR(9);
#pragma unroll
            for (int i = 0; i < 4; i++) {
                mma16816(acc[(2 * i) & 3], vf[2 * i], bb[i].x, bb[i].y);
                mma16816(acc[(2 * i + 1) & 3], vf[2 * i + 1], bb[i].z, bb[i].w);
            }
#pragma unroll
            for (int i = 0; i < 4; i++) {
                mma16816(acc[(2 * i) & 3], vf[8 + 2 * i], bc[i].x, bc[i].y);
                mma16816(acc[(2 * i + 1) & 3], vf[8 + 2 * i + 1], bc[i].z, bc[i].w);
            }
#pragma unroll
            for (int i = 0; i < 4; i++) acc[0][i] = (acc[0][i] + acc[1][i]) + (acc[2][i] + acc[3][i]);
            stx1_if(gs + k.y, acc[0][0], acc[0][2], tag, fl & 16u);
            stx1_if(gs + k.y + 128, acc[0][1], acc[0][3], tag, fl & 16u);
            c_out = clk();
            TR(10);
        }
        {
            const uint4 k = lds_v4(tb + 4096), k4 = lds_v4(tb + 4 * 4096);
            const uint32_t o_c = lds_v4(tb + 3 * 4096).w;
            bool landed = it != 0;
            if (w < 4) {
                uint4 v[4];
                uint2 ml[4];
                float w0, w1, w2, w3;
                if (it == 0) {
                    if (w == 0) prewait<4, 4 * PB>(gs + k4.x + (O_FLV - O_ML), tag); bar_sync<NB_LD, 128>(); }
                int n = 0;
                landed = __all_sync(~0u, mbar_test(bars + 8 * MB_WO));
#pragma unroll 1
                do {
                    wait_until(c_out, DLY_ML);
                    issue<4, 4 * PB>(ml, gs + k4.x);
                    wait_until(c_out, DLY_O);
                    TR(11);
                    issue<4, 4 * PB>(v, gs + o_c);
                    ldw<8>(wf, k.z + (SM_WO - SM_WQ));
                    float M = fmaxf(fmaxf(F(ml[0].y), F(ml[1].y)), fmaxf(F(ml[2].y), F(ml[3].y)));
                    M = fmaxf(M, __shfl_xor_sync(~0u, M, 8));
                    M = fmaxf(M, __shfl_xor_sync(~0u, M, 16));
                    w0 = ex2(F(ml[0].y) - M); w1 = ex2(F(ml[1].y) - M); w2 = ex2(F(ml[2].y) - M); w3 = ex2(F(ml[3].y) - M);
                    float L = fmaf(w0, F(ml[0].x), w1 * F(ml[1].x)) + fmaf(w2, F(ml[2].x), w3 * F(ml[3].x));
                    L += __shfl_xor_sync(~0u, L, 8);
                    L += __shfl_xor_sync(~0u, L, 16);
                    const float inv = rcp(L);
                    w0 *= inv; w1 *= inv; w2 *= inv; w3 *= inv;
                } while (missing2<4>(ml, v, tag + ((w0 + w1) + (w2 + w3) < -1.f ? 1u : 0u)) && ++n < POLL_LIMIT);
                TR(12);
                float4 o;
                o.x = fmaf(w0, F(v[0].x), w1 * F(v[1].x)) + fmaf(w2, F(v[2].x), w3 * F(v[3].x));
                o.y = fmaf(w0, F(v[0].y), w1 * F(v[1].y)) + fmaf(w2, F(v[2].y), w3 * F(v[3].y));
                o.z = fmaf(w0, F(v[0].z), w1 * F(v[1].z)) + fmaf(w2, F(v[2].z), w3 * F(v[3].z));
                o.w = fmaf(w0, F(v[0].w), w1 * F(v[1].w)) + fmaf(w2, F(v[2].w), w3 * F(v[3].w));
                sts_chunk(a_xs + XS_O, ar43(o));
            } else {
                ldw<8>(wf, k.z + (SM_WO - SM_WQ));
            }
            if (!landed) { mbar_wait(bars + 8 * MB_WO); ldw<8>(wf, k.z + (SM_WO - SM_WQ)); }
            bar_sync<NB_B, 256>();
            float d0[4] = {0.f, 0.f, 0.f, 0.f}, d1[4] = {0.f, 0.f, 0.f, 0.f}, d2[4] = {0.f, 0.f, 0.f, 0.f}, d3[4] = {0.f, 0.f, 0.f, 0.f};
#pragma unroll
            for (int i = 0; i < 4; i++) lds_v4_if(bb[i], a_bf + XS_O + i * 256, fl & 1u);
#pragma unroll
            for (int i = 0; i < 4; i += 2) {
                mma16816(d0, wf[2 * i], bb[i].x, bb[i].y);
                mma16816(d1, wf[2 * i + 1], bb[i].z, bb[i].w);
                mma16816(d2, wf[2 * i + 2], bb[i + 1].x, bb[i + 1].y);
                mma16816(d3, wf[2 * i + 3], bb[i + 1].z, bb[i + 1].w);
            }
#pragma unroll
            for (int i = 0; i < 4; i++) d0[i] = (d0[i] + d1[i]) + (d2[i] + d3[i]);
            stx1_if(gs + k.y + (O_RECD - O_RECB), d0[0] + d0[1], d0[2] + d0[3], tag, fl & 4u);
            c_out = clk();
            TR(13);
        }
        {
            const uint4 k = lds_v4(tb + 4 * 4096);
            if (w < 2) {
                float4 xr;
                uint4 v[8];
                wait_until(c_out, DLY_F1);
                if (it == 0) mbar_wait(bars + 8 * MB_W13A);
                TR(14);
                int n = 0;
#pragma unroll 1
                do {
                    issue<8, 16 * PB>(v, gs + k.y);
                    ldw<4>(wf, k.w); ldw<4>(wf + 4, k.w + 16384);
                    bb[0] = lds_v4(sb + SM_ONES);
                    bb[1] = lds_v4(sb + SM_ONES);
                    xr = lds_f4(a_xr + (b0_ & 1) * 256);
                } while (missing<8>(v, tag) && ++n < POLL_LIMIT);
                TR(15);
                float4 x = ar43(sum_v<8>(v));
                x.x += xr.x; x.y += xr.y; x.z += xr.z; x.w += xr.w;
                sts_chunk(a_xs + XS_F1, x);
                sts_v4(a_xr + (SM_XR2 - SM_XR), __float_as_uint(x.x), __float_as_uint(x.y), __float_as_uint(x.z), __float_as_uint(x.w));
            } else {
                ldw<4>(wf, k.w); ldw<4>(wf + 4, k.w + 16384);
                bb[0] = lds_v4(sb + SM_ONES);
                bb[1] = lds_v4(sb + SM_ONES);
            }
            if (it == 0) {
                mbar_wait(bars + 8 * MB_W13A); mbar_wait(bars + 8 * MB_W13);
                ldw<4>(wf, k.w); ldw<4>(wf + 4, k.w + 16384);
            }
            bar_sync<NB_BX, 288>();
            {
                float dg[4] = {0.f, 0.f, 0.f, 0.f}, du[4] = {0.f, 0.f, 0.f, 0.f};
                float dg1[4] = {0.f, 0.f, 0.f, 0.f}, du1[4] = {0.f, 0.f, 0.f, 0.f};
                lds_v4_if(bb[0], a_bf + XS_F1, fl & 1u);
                lds_v4_if(bb[1], a_bf + XS_F1 + 256, fl & 1u);
                mma16816(dg, wf[0], bb[0].x, bb[0].y);
                mma16816(du, wf[4], bb[0].x, bb[0].y);
                mma16816(dg1, wf[1], bb[0].z, bb[0].w);
                mma16816(du1, wf[5], bb[0].z, bb[0].w);
                mma16816(dg, wf[2], bb[1].x, bb[1].y);
                mma16816(du, wf[6], bb[1].x, bb[1].y);
                mma16816(dg1, wf[3], bb[1].z, bb[1].w);
                mma16816(du1, wf[7], bb[1].z, bb[1].w);
                const float h = (fl & 4u) ? 1.f : 0.f;
                const float g0 = fmaf(h, dg[1] + dg1[1], dg[0] + dg1[0]), g1 = fmaf(h, dg[3] + dg1[3], dg[2] + dg1[2]);
                const float u0 = fmaf(h, du[1] + du1[1], du[0] + du1[0]), u1 = fmaf(h, du[3] + du1[3], du[2] + du1[2]);
                stx2_if(gs + k.z, g0, g1, u0, u1, tag, w < 7 ? fl & exp_mask : 0u);
            }
            c_out = clk();
            TR(16);
        }
        {
            const uint4 k = lds_v4(tb + 5 * 4096);
            const uint32_t a0 = lds_v4(tb + 4 * 4096).w + (SM_W2 - SM_W1) - (w >> 2) * 8192;
            bool landed = it != 0;
            float2 xr = make_float2(0.f, 0.f);
            if (b0_ < 8) xr = lds_f2(k.w);
            if (w < 7) {
                const bool b4 = fl & 128u, b3 = fl & 256u;
                const float* pa = gs + k.x;
                const float* ps = gs + ((b0_ & ~7) + ((t0_ >> 3) & 3)) * PB + O_STF;
                uint4 v[2];
                uint2 st[2];
                wait_until(c_out, DLY_F2);
                TR(17);
                const uint32_t a_cs = sb + SM_CSF + t0_ * 8;
                float2 cs = lds_f2(a_cs);
                uint4 cv[2];
                const float* pc = pa + (it == 0 ? O_CSE - O_RECE : 0);
                int n = 0;
                landed = __all_sync(~0u, mbar_test(bars + 8 * MB_W2));
#pragma unroll 1
                do {
                    issue<2, 4 * PB>(st, ps);
                    issue<2, 4 * PB>(v, pa);
                    if (it == 0) issue<2, 4 * PB>(cv, pc); else { cv[0] = make_uint4(tag, 0u, tag, 0u); cv[1] = cv[0]; }
                    ldw<7>(wf, a0);
                } while (missing3(st, v, cv, tag) && ++n < POLL_LIMIT);
                TR(18);
                if (it == 0) {
                    const float4 u = ar43(sum_v<2>(cv));
                    cs.x = b4 ? u.y : u.x;
                    cs.y = b4 ? u.w : u.z;
                    sts_v2(a_cs, __float_as_uint(cs.x), __float_as_uint(cs.y));
                }
                const float4 u0 = sum_v<2>(v);
                float S = F(st[0].x) + F(st[1].x);
                float T = fmaf(fmaf(F(st[0].x), F(st[0].x), F(st[1].x) * F(st[1].x)), 1.f / 64.f, F(st[0].y) + F(st[1].y));
                float G = (b4 ? u0.y : u0.x) + __shfl_xor_sync(~0u, b4 ? u0.x : u0.y, 16);
                float U = (b4 ? u0.w : u0.z) + __shfl_xor_sync(~0u, b4 ? u0.z : u0.w, 16);
                S += __shfl_xor_sync(~0u, S, 16);
                T += __shfl_xor_sync(~0u, T, 16);
                S += __shfl_xor_sync(~0u, S, 8);
                T += __shfl_xor_sync(~0u, T, 8);
                G += __shfl_xor_sync(~0u, G, 8);
                U += __shfl_xor_sync(~0u, U, 8);
                const float mean = S * (1.f / 512.f);
                const float rstd = rsq(fmaxf(fmaf(-mean, mean, T * (1.f / 512.f)), 0.f) + 1e-5f);
                G = rstd * fmaf(-mean, cs.x, G);
                U = rstd * fmaf(-mean, cs.y, U);
                const float hv = G * rcp(1.f + ex2(-1.4426950408889634f * G)) * U;
                const uint32_t hh = pack_bf16(hv, 0.f), ll = pack_bf16(hv - F(hh << 16), 0.f);
                sts_u16(k.z, (uint16_t)(b3 ? ll : hh));
            } else {
                ldw<7>(wf, a0);
            }
            if (!landed) { mbar_wait(bars + 8 * MB_W2); ldw<7>(wf, a0); }
            bar_sync<NB_B, 256>();
            if (w < 4) {
                float d0[4] = {0.f, 0.f, 0.f, 0.f}, d1[4] = {0.f, 0.f, 0.f, 0.f}, d2[4] = {0.f, 0.f, 0.f, 0.f}, d3[4] = {0.f, 0.f, 0.f, 0.f};
#pragma unroll
                for (int i = 0; i < 4; i++) lds_v4_if(bb[i], a_bf + XS_F2 + i * 256, fl & 1u);
                mma16816(d0, wf[0], bb[0].x, bb[0].y);
                mma16816(d1, wf[1], bb[0].z, bb[0].w);
                mma16816(d2, wf[2], bb[1].x, bb[1].y);
                mma16816(d3, wf[3], bb[1].z, bb[1].w);
                mma16816(d0, wf[4], bb[2].x, bb[2].y);
                mma16816(d1, wf[5], bb[2].z, bb[2].w);
                mma16816(d2, wf[6], bb[3].x, bb[3].y);
#pragma unroll
                for (int i = 0; i < 4; i++) d0[i] = (d0[i] + d1[i]) + (d2[i] + d3[i]);
                stx1_if(gs + k.y, (d0[0] + d0[1]) + xr.x, (d0[2] + d0[3]) + xr.y, tag, fl & 4u);
            }
            if (it == 1 && t0_ == 255) sts_f(sb + SM_STOP, 1.f);
            c_out = clk();
            TR(19);
        }
        tagp = tag;
        tag = next_tag(tag);
    }
    if (b0_ == 0 && t0_ == 0) stg_u32(gs + O_EPOCH, ep == 2u ? 0u : ep + 1u);
}

typedef CUresult (*EncodeFn)(CUtensorMap*, CUtensorMapDataType, cuuint32_t, void*, const cuuint64_t*, const cuuint64_t*,
                             const cuuint32_t*, const cuuint32_t*, CUtensorMapInterleave, CUtensorMapSwizzle,
                             CUtensorMapL2promotion, CUtensorMapFloatOOBfill);

void make_map(EncodeFn enc, CUtensorMap* m, const void* p, uint64_t cols, uint64_t rows, uint32_t box_rows) {
    cuuint64_t dims[2] = {cols, rows};
    cuuint64_t strides[1] = {cols * 2};
    cuuint32_t box[2] = {64, box_rows};
    cuuint32_t es[2] = {1, 1};
    enc(m, CU_TENSOR_MAP_DATA_TYPE_BFLOAT16, 2, const_cast<void*>(p), dims, strides, box, es, CU_TENSOR_MAP_INTERLEAVE_NONE,
        CU_TENSOR_MAP_SWIZZLE_128B, CU_TENSOR_MAP_L2_PROMOTION_NONE, CU_TENSOR_MAP_FLOAT_OOB_FILL_NONE);
}

}

extern "C" void kernel_launch(void* const* d_in, const int* in_sizes, int n_in, void* d_out, int out_size) {
    (void)in_sizes; (void)n_in; (void)out_size;
    static EncodeFn enc = nullptr;
    static float* scratch = nullptr;
    if (!enc) {
        void* fn = nullptr;
        cudaDriverEntryPointQueryResult st;
        cudaGetDriverEntryPoint("cuTensorMapEncodeTiled", &fn, cudaEnableDefault, &st);
        enc = (EncodeFn)fn;
        cudaGetSymbolAddress((void**)&scratch, g_s);
        cudaFuncSetAttribute(fused_decode_kernel, cudaFuncAttributeMaxDynamicSharedMemorySize, SM_TOTAL);
    }
    Maps maps;
    make_map(enc, &maps.k, d_in[1], 128, 8ull * SK, 64);
    make_map(enc, &maps.v, d_in[2], 128, 8ull * SK, 64);
    make_map(enc, &maps.wo, d_in[4], 512, 4096, 64);
    make_map(enc, &maps.w1, d_in[6], 1792, 512, 64);
    make_map(enc, &maps.w3, d_in[7], 1792, 512, 64);
    make_map(enc, &maps.w2, d_in[8], 512, 1792, 56);
    fused_decode_kernel<<<NCTA, NTHREADS, SM_TOTAL>>>((const __nv_bfloat16*)d_in[3], scratch, (const __nv_bfloat16*)d_in[0], (__nv_bfloat16*)d_out, maps);
}
```

```cpp
#include <cuda_runtime.h>
#include <cuda_bf16.h>
#include <cuda.h>
#include <stdint.h>

#define KTRACE 0
#define DEPTH 4
#define TAU 660
#define TOFF 1100
#define T8 6700
#define TAU2 760
#define KEEPALIVE 6
#define DLY_Q 350
#define DLY_END 300
#define DLY_A 250
#define DLY_O 250
#define DLY_ML 150
#define DLY_F1 450
#define DLY_F2 450

namespace {

constexpr int NCTA = 128;
constexpr int NTHREADS = 384;
constexpr int SK = 32768, WIN = 4096;

constexpr int SM_WQ = 0;
constexpr int SM_K = 32768;
constexpr int SM_V = 98304;
constexpr int SM_WO = 163840;
constexpr int SM_W1 = SM_K;
constexpr int SM_W2 = SM_K + 32768;
constexpr int SM_MISC = 196608;
constexpr int SM_XS = SM_MISC;
constexpr int XS_Q = 0, XS_O = 1024, XS_F1 = 2048, XS_F2 = 3072;
constexpr int SM_QS = SM_XS + 4096;
constexpr int SM_PS = SM_QS + 1024;
constexpr int SM_LP = SM_PS + 2048;
constexpr int SM_MW = SM_LP + 1024;
constexpr int SM_XR = SM_MW + 128;
constexpr int SM_XR2 = SM_XR + 512;
constexpr int SM_STOP = SM_XR2 + 256;
constexpr int SM_ONES = SM_STOP + 16;
constexpr int SM_BAR = SM_ONES + 16;
constexpr int MB_K = 0, MB_V = 4, MB_WO = 8, MB_W13 = 10, MB_W2 = 11, MB_KFREE = 12, MB_W13A = 13;
constexpr int SM_TAB = SM_BAR + 128 + 96;
constexpr int SM_CSF = SM_V;
constexpr int SM_DUMMY = SM_TAB + 6 * 4096;
constexpr int SM_TOTAL = SM_DUMMY + 256;
static_assert(SM_TAB % 16 == 0 && SM_TOTAL <= 232448, "smem");
constexpr int NB_INIT = 1, NB_B = 2, NB_BX = 3, NB_P = 4, NB_SVC = 5, NB_LD = 6;

constexpr int O_RECA = 0;
constexpr int O_STQ = 64;
constexpr int O_ML = 96;
constexpr int O_RECB = 128;
constexpr int O_CSB = 256;
constexpr int O_RECD = 384;
constexpr int O_RECC = 512;
constexpr int O_RECE = 1024;
constexpr int O_STF = 1248;
constexpr int O_CSE = 1280;
constexpr int O_FLV = 1504;
constexpr int PB = 1568;
constexpr int O_EPOCH = NCTA * PB;
constexpr int O_END = O_EPOCH + 32;
__device__ __align__(1024) float g_s[O_END];

struct Maps { CUtensorMap k, v, wo, w1, w3, w2; };

__device__ __forceinline__ uint32_t smem_u32(const void* p) { return (uint32_t)__cvta_generic_to_shared(p); }
__device__ __forceinline__ void mbar_init(uint32_t bar, uint32_t cnt) {
    asm volatile("mbarrier.init.shared::cta.b64 [%0], %1;" ::"r"(bar), "r"(cnt) : "memory");
}
__device__ __forceinline__ void mbar_expect_tx(uint32_t bar, uint32_t bytes) {
    asm volatile("mbarrier.arrive.expect_tx.shared::cta.b64 _, [%0], %1;" ::"r"(bar), "r"(bytes) : "memory");
}
__device__ __forceinline__ void mbar_arrive(uint32_t bar) {
    asm volatile("mbarrier.arrive.shared::cta.b64 _, [%0];" ::"r"(bar) : "memory");
}
__device__ __forceinline__ bool mbar_try(uint32_t bar) {
    uint32_t ok;
    asm volatile("{\n.reg .pred p;\nmbarrier.try_wait.parity.shared::cta.b64 p, [%1], 0;\nselp.u32 %0, 1, 0, p;\n}"
                 : "=r"(ok) : "r"(bar) : "memory");
    return ok != 0;
}
__device__ __forceinline__ bool mbar_test(uint32_t bar) {
    uint32_t ok;
    asm volatile("{\n.reg .pred p;\nmbarrier.test_wait.parity.shared::cta.b64 p, [%1], 0;\nselp.u32 %0, 1, 0, p;\n}"
                 : "=r"(ok) : "r"(bar) : "memory");
    return ok != 0;
}
__device__ __forceinline__ void mbar_wait(uint32_t bar) {
    int n = 0;
#pragma unroll 1
    while (!mbar_try(bar) && ++n < (1 << 17)) { }
}
__device__ __forceinline__ void tma2d(uint32_t dst, const CUtensorMap* m, int c0, int c1, uint32_t bar) {
    asm volatile("cp.async.bulk.tensor.2d.shared::cluster.global.mbarrier::complete_tx::bytes [%0], [%1, {%3, %4}], [%2];"
                 ::"r"(dst), "l"((uint64_t)m), "r"(bar), "r"(c0), "r"(c1) : "memory");
}
template <int ID, int N> __device__ __forceinline__ void bar_sync() { asm volatile("bar.sync %0, %1;" ::"n"(ID), "n"(N) : "memory"); }
__device__ __forceinline__ void init_fence() {
    asm volatile("fence.mbarrier_init.release.cluster;" ::: "memory");
    asm volatile("fence.proxy.async.shared::cta;" ::: "memory");
}
__device__ __forceinline__ uint32_t ldg_u32(const void* p) {
    uint32_t v;
    asm volatile("ld.relaxed.gpu.global.u32 %0, [%1];" : "=r"(v) : "l"(p) : "memory");
    return v;
}
__device__ __forceinline__ void stg_u32(void* p, uint32_t v) {
    asm volatile("st.relaxed.gpu.global.u32 [%0], %1;" ::"l"(p), "r"(v) : "memory");
}
__device__ __forceinline__ void ldx(uint4& v, const void* p) {
    asm volatile("{\n.reg .b64 a, b;\nld.relaxed.gpu.global.v2.b64 {a, b}, [%4];\nmov.b64 {%0,%1}, a;\nmov.b64 {%2,%3}, b;\n}"
                 : "=r"(v.x), "=r"(v.y), "=r"(v.z), "=r"(v.w) : "l"(p) : "memory");
}
__device__ __forceinline__ void ldx(uint2& v, const void* p) {
    asm volatile("{\n.reg .b64 a;\nld.relaxed.gpu.global.b64 a, [%2];\nmov.b64 {%0,%1}, a;\n}" : "=r"(v.x), "=r"(v.y) : "l"(p) : "memory");
}
__device__ __forceinline__ uint32_t tagf(float v, uint32_t tag) { return (__float_as_uint(v) & ~3u) | tag; }
__device__ __forceinline__ void stx1(void* p, float a, float b, uint32_t tag) {
    asm volatile("{\n.reg .b64 a;\nmov.b64 a, {%1,%2};\nst.relaxed.gpu.global.b64 [%0], a;\n}"
                 ::"l"(p), "r"(tagf(a, tag)), "r"(__float_as_uint(b)) : "memory");
}
__device__ __forceinline__ void stx1_if(void* p, float a, float b, uint32_t tag, uint32_t q) {
    asm volatile("{\n.reg .pred q;\n.reg .b64 a;\nsetp.ne.u32 q, %3, 0;\nmov.b64 a, {%1,%2};\n@q st.relaxed.gpu.global.b64 [%0], a;\n}"
                 ::"l"(p), "r"(tagf(a, tag)), "r"(__float_as_uint(b)), "r"(q) : "memory");
}
__device__ __forceinline__ void stx2_if(void* p, float a, float b, float c, float d, uint32_t tag, uint32_t q) {
    asm volatile("{\n.reg .pred q;\n.reg .b64 a, b;\nsetp.ne.u32 q, %5, 0;\nmov.b64 a, {%1,%2};\nmov.b64 b, {%3,%4};\n@q st.relaxed.gpu.global.v2.b64 [%0], {a, b};\n}"
                 ::"l"(p), "r"(tagf(a, tag)), "r"(__float_as_uint(b)), "r"(tagf(c, tag)), "r"(__float_as_uint(d)), "r"(q) : "memory");
}
__device__ __forceinline__ void stx2(void* p, float a, float b, float c, float d, uint32_t tag) {
    asm volatile("{\n.reg .b64 a, b;\nmov.b64 a, {%1,%2};\nmov.b64 b, {%3,%4};\nst.relaxed.gpu.global.v2.b64 [%0], {a, b};\n}"
                 ::"l"(p), "r"(tagf(a, tag)), "r"(__float_as_uint(b)), "r"(tagf(c, tag)), "r"(__float_as_uint(d)) : "memory");
}
__device__ __forceinline__ void lds_v4_if(uint4& v, uint32_t a, uint32_t p) {
    asm volatile("{\n.reg .pred q;\nsetp.ne.u32 q, %5, 0;\n@q ld.shared.v4.u32 {%0,%1,%2,%3}, [%4];\n}"
                 : "+r"(v.x), "+r"(v.y), "+r"(v.z), "+r"(v.w) : "r"(a), "r"(p) : "memory");
}
__device__ __forceinline__ uint4 lds_v4(uint32_t a) {
    uint4 v;
    asm volatile("ld.shared.v4.u32 {%0,%1,%2,%3}, [%4];" : "=r"(v.x), "=r"(v.y), "=r"(v.z), "=r"(v.w) : "r"(a) : "memory");
    return v;
}
__device__ __forceinline__ void sts_v4(uint32_t a, uint32_t x, uint32_t y, uint32_t z, uint32_t w) {
    asm volatile("st.shared.v4.u32 [%0], {%1,%2,%3,%4};" ::"r"(a), "r"(x), "r"(y), "r"(z), "r"(w) : "memory");
}
__device__ __forceinline__ void sts_v2(uint32_t a, uint32_t x, uint32_t y) {
    asm volatile("st.shared.v2.u32 [%0], {%1,%2};" ::"r"(a), "r"(x), "r"(y) : "memory");
}
__device__ __forceinline__ float4 lds_f4(uint32_t a) {
    float4 v;
    asm volatile("ld.shared.v4.f32 {%0,%1,%2,%3}, [%4];" : "=f"(v.x), "=f"(v.y), "=f"(v.z), "=f"(v.w) : "r"(a) : "memory");
    return v;
}
__device__ __forceinline__ float2 lds_f2(uint32_t a) {
    float2 v;
    asm volatile("ld.shared.v2.f32 {%0,%1}, [%2];" : "=f"(v.x), "=f"(v.y) : "r"(a) : "memory");
    return v;
}
__device__ __forceinline__ float lds_f(uint32_t a) {
    float v;
    asm volatile("ld.shared.f32 %0, [%1];" : "=f"(v) : "r"(a) : "memory");
    return v;
}
__device__ __forceinline__ void sts_f(uint32_t a, float v) { asm volatile("st.shared.f32 [%0], %1;" ::"r"(a), "f"(v) : "memory"); }
__device__ __forceinline__ void sts_u16(uint32_t a, uint16_t v) { asm volatile("st.shared.u16 [%0], %1;" ::"r"(a), "h"(v) : "memory"); }
__device__ __forceinline__ void ldsm4(uint32_t* r, uint32_t a) {
    asm volatile("ldmatrix.sync.aligned.m8n8.x4.shared.b16 {%0,%1,%2,%3}, [%4];"
                 : "=r"(r[0]), "=r"(r[1]), "=r"(r[2]), "=r"(r[3]) : "r"(a) : "memory");
}
__device__ __forceinline__ void ldsm4t(uint32_t* r, uint32_t a) {
    asm volatile("ldmatrix.sync.aligned.m8n8.x4.trans.shared.b16 {%0,%1,%2,%3}, [%4];"
                 : "=r"(r[0]), "=r"(r[1]), "=r"(r[2]), "=r"(r[3]) : "r"(a) : "memory");
}
template <int N>
__device__ __forceinline__ void ldw(uint32_t (*wf)[4], uint32_t a) {
#pragma unroll
    for (int s = 0; s < N; s++) ldsm4t(wf[s], a + s * 2048);
}
__device__ __forceinline__ void mma16816(float* d, const uint32_t* a, uint32_t b0, uint32_t b1) {
    asm("mma.sync.aligned.m16n8k16.row.col.f32.bf16.bf16.f32 {%0,%1,%2,%3}, {%4,%5,%6,%7}, {%8,%9}, {%0,%1,%2,%3};"
        : "+f"(d[0]), "+f"(d[1]), "+f"(d[2]), "+f"(d[3])
        : "r"(a[0]), "r"(a[1]), "r"(a[2]), "r"(a[3]), "r"(b0), "r"(b1));
}
__device__ __forceinline__ float ex2(float x) { float y; asm("ex2.approx.ftz.f32 %0, %1;" : "=f"(y) : "f"(x)); return y; }
__device__ __forceinline__ float F(uint32_t u) { return __uint_as_float(u); }
__device__ __forceinline__ uint32_t pack_bf16(float lo, float hi) {
    uint32_t r;
    asm("cvt.rn.bf16x2.f32 %0, %1, %2;" : "=r"(r) : "f"(hi), "f"(lo));
    return r;
}
#define POLL_LIMIT (1 << 18)
__device__ __forceinline__ uint32_t clk() { uint32_t c; asm volatile("mov.u32 %0, %%clock;" : "=r"(c)); return c; }
__device__ __forceinline__ void wait_until(uint32_t c0, uint32_t d) { while (clk() - c0 < d) { } }
__device__ __forceinline__ uint32_t bad(const uint4& a, uint32_t tag) { return (a.x ^ tag) | (a.z ^ tag); }
__device__ __forceinline__ uint32_t bad(const uint2& a, uint32_t tag) { return a.x ^ tag; }
template <int N, int S, typename V>
__device__ __forceinline__ void issue(V* v, const float* p) {
#pragma unroll
    for (int i = 0; i < N; i++) ldx(v[i], p + i * S);
}
template <int N, typename V>
__device__ __forceinline__ bool missing(const V* v, uint32_t tag) {
    uint32_t any = 0;
#pragma unroll
    for (int i = 0; i < N; i++) any |= bad(v[i], tag);
    return __any_sync(~0u, (any & 3u) != 0);
}
template <int N>
__device__ __forceinline__ bool missing2(const uint2* a, const uint4* v, uint32_t tag) {
    uint32_t any = 0;
#pragma unroll
    for (int i = 0; i < N; i++) any |= bad(a[i], tag) | bad(v[i], tag);
    return __any_sync(~0u, (any & 3u) != 0);
}
__device__ __forceinline__ bool missing3(const uint2* a, const uint4* v, const uint4* u, uint32_t tag) {
    const uint32_t any = (bad(a[0], tag) | bad(a[1], tag)) | (bad(v[0], tag) | bad(v[1], tag)) | (bad(u[0], tag) | bad(u[1], tag));
    return __any_sync(~0u, (any & 3u) != 0);
}
__device__ __forceinline__ float rcp(float x) { float y; asm("rcp.approx.ftz.f32 %0, %1;" : "=f"(y) : "f"(x)); return y; }
__device__ __forceinline__ float rsq(float x) { float y; asm("rsqrt.approx.ftz.f32 %0, %1;" : "=f"(y) : "f"(x)); return y; }
template <int N, int S>
__device__ __forceinline__ void prewait(const float* p, uint32_t tag) {
    uint2 u[N];
#pragma unroll 1
    for (int n = 0; n < POLL_LIMIT; n++) {
        issue<N, S>(u, p);
        if (!missing<N>(u, tag)) break;
        __nanosleep(20);
    }
}
template <int N, int S, typename V>
__device__ __forceinline__ void fetch(V* v, const float* p, uint32_t tag) {
    int n = 0;
#pragma unroll 1
    do { issue<N, S>(v, p); } while (missing<N>(v, tag) && ++n < POLL_LIMIT);
}
template <int N>
__device__ __forceinline__ float4 sum_v(const uint4* v) {
    if constexpr (N == 1) {
        return make_float4(F(v[0].x), F(v[0].y), F(v[0].z), F(v[0].w));
    } else {
        const float4 a = sum_v<N / 2>(v), b = sum_v<N / 2>(v + N / 2);
        return make_float4(a.x + b.x, a.y + b.y, a.z + b.z, a.w + b.w);
    }
}
__device__ __forceinline__ float4 ar43(float4 v) {
#pragma unroll
    for (int o = 16; o >= 8; o >>= 1) {
        v.x += __shfl_xor_sync(~0u, v.x, o); v.y += __shfl_xor_sync(~0u, v.y, o);
        v.z += __shfl_xor_sync(~0u, v.z, o); v.w += __shfl_xor_sync(~0u, v.w, o);
    }
    return v;
}
__device__ __forceinline__ int map_f(float v) { const int i = __float_as_int(v); return i ^ ((i >> 31) & 0x7fffffff); }
__device__ __forceinline__ float unmap_f(int i) { return __int_as_float(i ^ ((i >> 31) & 0x7fffffff)); }
constexpr float SM_SCALE = 0.08838834764831845f * 1.4426950408889634f;
__device__ __forceinline__ uint32_t next_tag(uint32_t tag) { return tag == 3u ? 1u : tag + 1u; }
__device__ __forceinline__ void sts_chunk(uint32_t a, const float4& v) {
    const uint32_t h0 = pack_bf16(v.x, v.z), h1 = pack_bf16(v.y, v.w);
    sts_v2(a, h0, h1);
    sts_v2(a + 64, pack_bf16(v.x - F(h0 << 16), v.z - F(h0 & 0xffff0000u)), pack_bf16(v.y - F(h1 << 16), v.w - F(h1 & 0xffff0000u)));
}

#define TR(i) do { } while (0)

__global__ void __launch_bounds__(NTHREADS, 1)
fused_decode_kernel(const __nv_bfloat16* __restrict__ wq, float* __restrict__ gs, const __nv_bfloat16* __restrict__ x0,
                    __nv_bfloat16* __restrict__ out, const __grid_constant__ Maps maps) {
    extern __shared__ __align__(1024) unsigned char smem_raw[];
    const uint32_t sb = smem_u32(smem_raw);
    const int b0_ = blockIdx.x, t0_ = threadIdx.x;
    unsigned long long g0 = 0;
    if (t0_ < 256) {
        const int b = b0_, t = t0_;
        const int hq = (b >> 4) * 4 + ((b >> 3) & 1) * 2 + (b & 1);
        const __nv_bfloat16* src = wq + (size_t)(((b >> 1) & 3) * 128 + (t >> 4)) * 4096 + hq * 128 + (t & 15) * 8;
        const uint32_t dst = sb + SM_WQ + ((t >> 3) & 1) * 16384 + (t >> 4) * 128 + (((t & 7) ^ ((t >> 4) & 7)) << 4);
#pragma unroll
        for (int i = 0; i < 8; i++)
            asm volatile("cp.async.cg.shared.global [%0], [%1], 16;" ::"r"(dst + i * 2048), "l"(src + (size_t)i * 16 * 4096) : "memory");
        asm volatile("cp.async.commit_group;" ::: "memory");
        stx2(gs + b * PB + t * 4, 0.f, 0.f, 0.f, 0.f, 0u);
        if (t * 4 + 1024 < PB) stx2(gs + b * PB + 1024 + t * 4, 0.f, 0.f, 0.f, 0.f, 0u);
    } else if (t0_ == 256) {
        asm volatile("mov.u64 %0, %%globaltimer;" : "=l"(g0));
        const int kvrow = (b0_ >> 4) * SK + (SK - WIN) + (b0_ & 15) * 256;
        mbar_init(sb + SM_BAR, 1);
        init_fence();
        mbar_expect_tx(sb + SM_BAR, 16384);
        tma2d(sb + SM_K, &maps.k, 0, kvrow, sb + SM_BAR);
        tma2d(sb + SM_K + 32768, &maps.k, 64, kvrow, sb + SM_BAR);
    }
    __syncwarp();
    const int wg = __shfl_sync(0xffffffffu, t0_ >> 7, 0);
    if (wg == 2) {
        asm volatile("setmaxnreg.dec.sync.aligned.u32 40;");
        const int b = b0_, w = t0_ >> 5, lane = t0_ & 31;
        const uint32_t bars = sb + SM_BAR;
        if (w == 8) {
            const int stag = (b >> 4) * (TAU / 8);
            auto pace = [&](int slot16) {
                const long long tgt = (long long)(slot16 * TAU / 16 + TOFF + stag);
                unsigned long long g;
                do { asm volatile("mov.u64 %0, %%globaltimer;" : "=l"(g)); } while ((long long)(g - g0) < tgt);
            };
            const int kvrow = (b >> 4) * SK + (SK - WIN) + (b & 15) * 256;
            auto kvchunk = [&](int c) {
                const CUtensorMap* m = (c >> 2) ? &maps.v : &maps.k;
                const uint32_t dst = sb + SM_K + (c >> 2) * 65536 + (c & 3) * 8192;
                mbar_expect_tx(bars + 8 * c, 16384);
                tma2d(dst, m, 0, kvrow + (c & 3) * 64, bars + 8 * c);
                tma2d(dst + 32768, m, 64, kvrow + (c & 3) * 64, bars + 8 * c);
            };
            bar_sync<NB_SVC, 128>();
            asm volatile("bar.arrive %0, 384;" ::"n"(NB_INIT) : "memory");
            if (lane == 0) {
#pragma unroll 1
                for (int c = 1; c < 8; c++) {
                    if (c >= DEPTH) mbar_wait(bars + 8 * (c - DEPTH));
                    pace(c * 16);
                    kvchunk(c);
                }
                const unsigned long long g1 = g0 + T8;
                mbar_expect_tx(bars + 8 * MB_WO, 32768);
                mbar_expect_tx(bars + 8 * MB_W13A, 16384);
                mbar_expect_tx(bars + 8 * MB_W13, 16384);
                mbar_expect_tx(bars + 8 * MB_W2, 14336);
#pragma unroll 1
                for (int i = 0; i < 10; i++) {
                    const int ph = i < 4 ? (b >> 2) * (TAU2 / 32) : i < 8 ? (b & 7) * (TAU2 / 8) : (b >> 3) * (TAU2 / 16);
                    unsigned long long g;
                    do { asm volatile("mov.u64 %0, %%globaltimer;" : "=l"(g)); } while ((long long)(g - g1) < (long long)((i & ~1) * (TAU2 / 2) + ph));
                    const int lo = i & 1, hi = (i >> 1) & 1;
                    if (i < 4) {
                        tma2d(sb + SM_WO + lo * 16384 + hi * 8192, &maps.wo, (b & 3) * 128 + lo * 64, (b >> 2) * 128 + hi * 64, bars + 8 * MB_WO);
                    } else if (i < 8) {
                        if (i == 4) mbar_wait(bars + 8 * MB_KFREE);
                        tma2d(sb + SM_W1 + lo * 16384 + hi * 8192, lo ? &maps.w3 : &maps.w1, (b >> 3) * 112 + hi * 64, (b & 7) * 64, bars + 8 * (hi ? MB_W13 : MB_W13A));
                    } else {
                        tma2d(sb + SM_W2 + lo * 7168, &maps.w2, (b & 7) * 64, (b >> 3) * 112 + lo * 56, bars + 8 * MB_W2);
                    }
                }
            }
            return;
        }
        if (lane == 0) {
#pragma unroll 1
            for (int i = 1 + (w - 9); i <= MB_W13A; i += 3) mbar_init(bars + 8 * i, i == MB_KFREE ? 8 : 1);
            init_fence();
        } else if (w == 11 && lane < 6) {
            asm volatile("prefetch.tensormap [%0];" ::"l"((uint64_t)(&maps.k + lane)) : "memory");
        }
        const unsigned ep = ldg_u32(gs + O_EPOCH);
        __syncwarp();
        bar_sync<NB_SVC, 128>();
        bar_sync<NB_INIT, 384>();
        uint32_t tag = (2u * ep) % 3u + 1u;
        if (w == 9) {
            float* const pq = gs + b * PB + O_STQ + (lane & 15) * 2;
            const uint32_t l16 = (lane & 15) * 16;
#pragma unroll 1
            for (int it = 0; it < 2; ++it) {
                {
                    bar_sync<NB_BX, 288>();
                    const float piv = lds_f(sb + SM_XR);
                    const float4 u = lds_f4(sb + SM_XR + l16), v = lds_f4(sb + SM_XR + 256 + l16);
                    const float a0 = u.x - piv, a1 = u.y - piv, a2 = u.z - piv, a3 = u.w - piv;
                    const float a4 = v.x - piv, a5 = v.y - piv, a6 = v.z - piv, a7 = v.w - piv;
                    float s1 = ((a0 + a1) + (a2 + a3)) + ((a4 + a5) + (a6 + a7));
                    float s2 = (fmaf(a0, a0, a1 * a1) + fmaf(a2, a2, a3 * a3)) + (fmaf(a4, a4, a5 * a5) + fmaf(a6, a6, a7 * a7));
#pragma unroll
                    for (int o = 8; o >= 1; o >>= 1) { s1 += __shfl_xor_sync(~0u, s1, o); s2 += __shfl_xor_sync(~0u, s2, o); }
                    stx1_if(pq, fmaf(128.f, piv, s1), fmaxf(fmaf(-s1 * (1.f / 128.f), s1, s2), 0.f), tag, lane < 16);
                }
                {
                    bar_sync<NB_BX, 288>();
                    const float piv = lds_f(sb + SM_XR2);
                    const float4 u = lds_f4(sb + SM_XR2 + (l16 & 127)), v = lds_f4(sb + SM_XR2 + 128 + (l16 & 127));
                    const float a0 = u.x - piv, a1 = u.y - piv, a2 = u.z - piv, a3 = u.w - piv;
                    const float a4 = v.x - piv, a5 = v.y - piv, a6 = v.z - piv, a7 = v.w - piv;
                    float s1 = ((a0 + a1) + (a2 + a3)) + ((a4 + a5) + (a6 + a7));
                    float s2 = (fmaf(a0, a0, a1 * a1) + fmaf(a2, a2, a3 * a3)) + (fmaf(a4, a4, a5 * a5) + fmaf(a6, a6, a7 * a7));
#pragma unroll
                    for (int o = 4; o >= 1; o >>= 1) { s1 += __shfl_xor_sync(~0u, s1, o); s2 += __shfl_xor_sync(~0u, s2, o); }
                    stx1_if(pq + (O_STF - O_STQ), fmaf(64.f, piv, s1), fmaxf(fmaf(-s1 * (1.f / 64.f), s1, s2), 0.f), tag, lane < 16);
                }
                tag = next_tag(tag);
            }
        } else if (w == 10) {
            float d[4] = {0.f, 0.f, 0.f, 0.f};
            bool told = false;
            mbar_wait(bars + 8 * (MB_V + 2));
#pragma unroll 1
            for (int n = 0; n < 1000; n++) {
                asm volatile("mma.sync.aligned.m16n8k16.row.col.f32.bf16.bf16.f32 {%0,%1,%2,%3}, {%4,%4,%4,%4}, {%4,%4}, {%0,%1,%2,%3};"
                             : "+f"(d[0]), "+f"(d[1]), "+f"(d[2]), "+f"(d[3]) : "r"(0u));
                bool stop = false;
#pragma unroll 1
                for (int j = 0; j < KEEPALIVE && !stop; j++) {
                    if (!told && mbar_test(bars + 8 * (MB_V + 3))) {
                        stx1_if(gs + b * PB + O_FLV + (lane & 15) * 2, 0.f, 0.f, tag, lane < 16);
                        told = true;
                    }
                    stop = lds_f(sb + SM_STOP) != 0.f;
                }
                if (stop) break;
            }
            if (d[0] == 123.456f) sts_f(sb + SM_STOP + 4, d[1]);
        } else {
#pragma unroll 1
            for (int it = 0; it < 2; ++it) {
                bar_sync<NB_P, 288>();
                const float M = unmap_f(__float_as_int(lds_f(sb + SM_MW + it * 16 + (lane & 3) * 4))) * SM_SCALE;
                const float4 l0 = lds_f4(sb + SM_LP + lane * 32), l1 = lds_f4(sb + SM_LP + lane * 32 + 16);
                float l = ((l0.x + l0.y) + (l0.z + l0.w)) + ((l1.x + l1.y) + (l1.z + l1.w));
                l += __shfl_xor_sync(~0u, l, 4);
                l += __shfl_xor_sync(~0u, l, 8);
                l += __shfl_xor_sync(~0u, l, 16);
                if (lane < 16) stx1(gs + b * PB + O_ML + lane * 2, l, M, tag);
                tag = next_tag(tag);
            }
        }
        return;
    }

    asm volatile("setmaxnreg.inc.sync.aligned.u32 232;");
    const uint32_t bars = sb + SM_BAR;
    const unsigned ep = ldg_u32(gs + O_EPOCH);
    {
        const int b = b0_, t = t0_, w = t >> 5, lane = t & 31, g = lane >> 2, c = lane & 3, pl = lane >> 3, ch = lane & 7;
        const int kc = 32 * (w & 3) + (ch >> 2) * 16 + 2 * (ch & 3);
        const __nv_bfloat16* xp = x0 + ((b >> 1) & 3) * 128 + kc;
        const uint32_t x01 = *reinterpret_cast<const uint32_t*>(xp), x89 = *reinterpret_cast<const uint32_t*>(xp + 8);
        const uint32_t lt = ((lane & 7) + ((lane >> 4) & 1) * 8) * 128 + ((((w & 3) * 2 + ((lane >> 3) & 1)) ^ (lane & 7)) << 4);
        const uint32_t o_exp = b * PB + w * 16 + g * 2, o_ld = (w & 3) * 32 + ch * 4;
        const uint32_t a_xs = sb + SM_XS + (w & 3) * 256 + (ch & 3) * 16 + (ch >> 2) * 8;
        const int hA = 2 * (c & 1);
        const uint32_t tb = sb + SM_TAB + t * 16;
        sts_v4(tb, sb + SM_XS + (lane & 15) * 16, a_xs, sb + SM_XR + o_ld * 4,
               (lane < 8 ? 1u : 0u) | (lane < 16 ? 2u : 0u) | (c == 0 ? 4u : 0u) | (c == 1 ? 8u : 0u) | (c < 2 ? 16u : 0u) | ((g & 1) ? 32u : 0u) |
               ((b < 16 && w == ((b >> 3) * 2 + (b & 1)) && pl == 0) ? 64u : 0u) | ((lane >> 4) ? 128u : 0u) | (((lane >> 3) & 1) ? 256u : 0u) | ((c & 1) ? 512u : 0u) | (lane < 4 ? 1024u : 0u) | (w << 16));
        sts_v4(tb + 4096, O_RECA + (pl * 8 + (b & 6) + ((w >> 1) & 1)) * PB + (o_ld & 63), (c == 0 ? O_RECB : O_CSB) + o_exp,
               sb + SM_WQ + (w >> 2) * 16384 + lt, ((b >> 1) & 3) * 128 + kc);
        sts_v4(tb + 2 * 4096, ((b & ~15) + ((w >> 1) & 1) * 8 + (w & 1)) * PB, O_RECC + b * PB + hA * 128 + w * 16 + g * 2,
               sb + SM_QS + ((g >> 1) * 4 + (w & 3)) * 64 + c * 16 + (g & 1) * 8, c < 2 ? sb + SM_PS + w * 256 + (hA * 4 + (g >> 1)) * 16 + (g & 1) * 4 : sb + SM_DUMMY + 4 * g + 128);
        sts_v4(tb + 3 * 4096, c < 2 ? sb + SM_LP + ((w * 4 + hA) * 8 + g) * 4 : sb + SM_DUMMY + 4 * g, sb + SM_MW + c * 4, sb + SM_MW + hA * 4,
                 ((b & ~15) + pl) * PB + O_RECC + ((b >> 2) & 3) * 128 + o_ld);
        sts_v4(tb + 4 * 4096, ((b & ~15) + pl) * PB + O_ML + ((b >> 2) & 3) * 2, O_RECD + (pl * 4 + ((b >> 1) & 3)) * PB + (b & 1) * 64 + (o_ld & 63),
               (c == 0 ? O_RECE : O_CSE) + b * PB + w * 32 + g * 4, sb + SM_W1 + (w >> 2) * 8192 + lt);
        sts_v4(tb + 5 * 4096, ((b & ~7) + pl) * PB + O_RECE + w * 32 + ch * 4, O_RECA + b * PB + (w & 3) * 16 + g * 2,
               sb + SM_XS + XS_F2 + (((w >> 1) * 4 + ((lane >> 3) & 1)) * 4 + (ch >> 1)) * 16 + ((w & 1) * 4 + (lane >> 4) * 2 + (ch & 1)) * 2,
               sb + SM_XR2 + ((w & 3) * 4 + (g >> 1)) * 16 + (g & 1) * 8);
        if (w < 4) sts_v4(sb + SM_XR + o_ld * 4, x01 << 16, x89 << 16, x01 & 0xffff0000u, x89 & 0xffff0000u);
        if (t == 0) sts_f(sb + SM_STOP, 0.f);
        if (t == 0) sts_v4(sb + SM_ONES, 0x3F803F80u, 0x3F803F80u, 0x3F803F80u, 0x3F803F80u);
        if (t < 2) sts_v4(sb + SM_MW + t * 16, 0x80000000u, 0x80000000u, 0x80000000u, 0x80000000u);
    }
    uint32_t kf[2][8][4], vf[16][4];

    bar_sync<NB_INIT, 384>();
    asm volatile("cp.async.wait_group 0;" ::: "memory");
    bar_sync<NB_B, 256>();
    const uint32_t tb = sb + SM_TAB + t0_ * 16;
    const uint4 cm = lds_v4(tb);
    const uint32_t a_bf = cm.x, a_xs = cm.y, a_xr = cm.z, fl = cm.w;
    const uint32_t w = fl >> 16;

    uint32_t tagp = 0;
    uint32_t tag = (2u * ep) % 3u + 1u;
    uint32_t c_out = clk();
#pragma unroll 1
    for (int it = 0; it < 3; ++it) {
        uint32_t wf[8][4];
        uint4 bb[4];
        const uint32_t exp_mask = it == 0 ? 12u : 4u;
        TR(0);
        {
            if (it == 2 && !__any_sync(~0u, fl & 64u)) break;
            const uint4 k = lds_v4(tb + 4096);
            if (w < 4) {
                float4 xv;
                if (it > 0) {
                    uint4 v[4];
                    wait_until(c_out, it == 2 ? DLY_END : DLY_Q);
                    TR(1);
                    int n = 0;
#pragma unroll 1
                    do {
                        issue<4, 32 * PB>(v, gs + k.x);
                        ldw<8>(wf, k.z);
#pragma unroll
                        for (int i = 0; i < 4; i++) bb[i] = lds_v4(sb + SM_ONES);
                    } while (missing<4>(v, tagp) && ++n < POLL_LIMIT);
                    TR(2);
                    xv = ar43(sum_v<4>(v));
                } else {
                    xv = lds_f4(a_xr);
                    ldw<8>(wf, k.z);
#pragma unroll
                    for (int i = 0; i < 4; i++) bb[i] = lds_v4(sb + SM_ONES);
                }
                if (it == 2) {
                    if (fl & 64u) {
                        *reinterpret_cast<uint32_t*>(out + k.w) = pack_bf16(xv.x, xv.z);
                        *reinterpret_cast<uint32_t*>(out + k.w + 8) = pack_bf16(xv.y, xv.w);
                    }
                    break;
                }
                sts_chunk(a_xs + XS_Q, xv);
                sts_v4(a_xr, __float_as_uint(xv.x), __float_as_uint(xv.y), __float_as_uint(xv.z), __float_as_uint(xv.w));
            } else {
                ldw<8>(wf, k.z);
#pragma unroll
                for (int i = 0; i < 4; i++) bb[i] = lds_v4(sb + SM_ONES);
            }
            bar_sync<NB_BX, 288>();
            float d0[4] = {0.f, 0.f, 0.f, 0.f}, d1[4] = {0.f, 0.f, 0.f, 0.f}, d2[4] = {0.f, 0.f, 0.f, 0.f}, d3[4] = {0.f, 0.f, 0.f, 0.f};
#pragma unroll
            for (int i = 0; i < 4; i++) lds_v4_if(bb[i], a_bf + XS_Q + i * 256, fl & 1u);
            TR(3);
#pragma unroll
            for (int i = 0; i < 4; i += 2) {
                mma16816(d0, wf[2 * i], bb[i].x, bb[i].y);
                mma16816(d1, wf[2 * i + 1], bb[i].z, bb[i].w);
                mma16816(d2, wf[2 * i + 2], bb[i + 1].x, bb[i + 1].y);
                mma16816(d3, wf[2 * i + 3], bb[i + 1].z, bb[i + 1].w);
            }
#pragma unroll
            for (int i = 0; i < 4; i++) d0[i] = (d0[i] + d1[i]) + (d2[i] + d3[i]);
            const float h = (fl & 4u) ? 1.f : 0.f;
            stx1_if(gs + k.y, fmaf(h, d0[1], d0[0]), fmaf(h, d0[3], d0[2]), tag, fl & exp_mask);
            c_out = clk();
            TR(4);
        }
        {
            const uint4 k = lds_v4(tb + 2 * 4096), k2 = lds_v4(tb + 3 * 4096);
            const uint32_t a_mr = k2.z + it * 16;
            if (it == 0) {
                const int lane = t0_ & 31, i8 = lane & 7;
                const int key = (i8 + 8 * (i8 & 1)) ^ ((lane >> 3) & 1);
                mbar_wait(bars + 8 * (MB_K + (w >> 1)));
                mbar_wait(bars + 8 * (MB_K + 2));
#pragma unroll
                for (int T = 0; T < 2; T++) {
                    const uint32_t rowa = sb + SM_K + (w * 32 + T * 16 + key) * 128;
#pragma unroll
                    for (int s = 0; s < 8; s++)
                        ldsm4(kf[T][s], rowa + (s >> 2) * 32768 + ((((s & 3) * 2 + (lane >> 4)) ^ (key & 7)) << 4));
                }
            }
            if (w < 4) {
                const float* pb = gs + k.x;
                const float* pa = pb + O_RECB + (t0_ & 31) * 4;
                const uint32_t a_cq = sb + SM_XS + (t0_ >> 3) * 256 + 128 + (t0_ & 7) * 16;
                uint4 v[4];
                uint2 st[4];
                wait_until(c_out, DLY_A);
                TR(5);
                if (it == 0) {
                    uint4 cv[4];
                    fetch<4, 2 * PB>(cv, pa + (O_CSB - O_RECB), tag);
                    const float4 u = sum_v<4>(cv);
                    sts_v4(a_cq, __float_as_uint(u.x), __float_as_uint(u.y), __float_as_uint(u.z), __float_as_uint(u.w));
                }
                const float4 csq = lds_f4(a_cq);
                float rstd, mr;
                int n = 0;
#pragma unroll 1
                do {
                    issue<4, 2 * PB>(st, pb + O_STQ);
                    issue<4, 2 * PB>(v, pa);
                    const float mean4 = ((F(st[0].x) + F(st[1].x)) + (F(st[2].x) + F(st[3].x))) * 0.25f;
                    const float e0 = F(st[0].x) - mean4, e1 = F(st[1].x) - mean4, e2 = F(st[2].x) - mean4, e3 = F(st[3].x) - mean4;
                    const float m2 = ((F(st[0].y) + F(st[1].y)) + (F(st[2].y) + F(st[3].y))) + ((e0 * e0 + e1 * e1) + (e2 * e2 + e3 * e3)) * (1.f / 128.f);
                    rstd = rsq(m2 * (1.f / 512.f) + 1e-5f);
                    mr = -mean4 * (1.f / 128.f) * rstd;
                } while (missing2<4>(st, v, tag + (rstd < -1.f ? 1u : 0u)) && ++n < POLL_LIMIT);
                TR(6);
                const float4 q = sum_v<4>(v);
                sts_v2(k.z, pack_bf16(fmaf(q.x, rstd, mr * csq.x), fmaf(q.z, rstd, mr * csq.z)), pack_bf16(fmaf(q.y, rstd, mr * csq.y), fmaf(q.w, rstd, mr * csq.w)));
            }
            bar_sync<NB_B, 256>();
            float s00[4] = {0.f, 0.f, 0.f, 0.f}, s01[4] = {0.f, 0.f, 0.f, 0.f}, s10[4] = {0.f, 0.f, 0.f, 0.f}, s11[4] = {0.f, 0.f, 0.f, 0.f};
#pragma unroll
            for (int i = 0; i < 4; i++) lds_v4_if(bb[i], a_bf + (SM_QS - SM_XS) + i * 256, fl & 2u);
            TR(7);
#pragma unroll
            for (int i = 0; i < 4; i++) {
                mma16816(s00, kf[0][2 * i], bb[i].x, bb[i].y);
                mma16816(s10, kf[1][2 * i], bb[i].x, bb[i].y);
                mma16816(s01, kf[0][2 * i + 1], bb[i].z, bb[i].w);
                mma16816(s11, kf[1][2 * i + 1], bb[i].z, bb[i].w);
            }
#pragma unroll
            for (int i = 0; i < 4; i++) { s00[i] += s01[i]; s10[i] += s11[i]; }
            {
                const bool od = fl & 32u;
                const float xA = fmaxf(fmaxf(s00[0], s00[2]), fmaxf(s10[0], s10[2])), xB = fmaxf(fmaxf(s00[1], s00[3]), fmaxf(s10[1], s10[3]));
                const float m = fmaxf(od ? xB : xA, __shfl_xor_sync(~0u, od ? xA : xB, 4));
                asm volatile("{\n.reg .pred q;\nsetp.ne.u32 q, %2, 0;\n@q red.shared.max.s32 [%0], %1;\n}"
                             ::"r"(a_mr + (od ? 4u : 0u)), "r"(map_f(m)), "r"(fl & 16u) : "memory");
            }
            bar_sync<NB_B, 256>();
            const float2 mm = lds_f2(a_mr);
            const float mA = unmap_f(__float_as_int(mm.x)) * SM_SCALE, mB = unmap_f(__float_as_int(mm.y)) * SM_SCALE;
            const bool od = fl & 32u;
            const float pA0 = ex2(fmaf(od ? s00[2] : s00[0], SM_SCALE, -mA)), pA1 = ex2(fmaf(od ? s00[0] : s00[2], SM_SCALE, -mA));
            const float pA2 = ex2(fmaf(od ? s10[2] : s10[0], SM_SCALE, -mA)), pA3 = ex2(fmaf(od ? s10[0] : s10[2], SM_SCALE, -mA));
            const float pB0 = ex2(fmaf(od ? s00[3] : s00[1], SM_SCALE, -mB)), pB1 = ex2(fmaf(od ? s00[1] : s00[3], SM_SCALE, -mB));
            const float pB2 = ex2(fmaf(od ? s10[3] : s10[1], SM_SCALE, -mB)), pB3 = ex2(fmaf(od ? s10[1] : s10[3], SM_SCALE, -mB));
            sts_f(k.w, F(pack_bf16(pA0, pA1)));
            sts_f(k.w + 8, F(pack_bf16(pA2, pA3)));
            sts_f(k.w + 64, F(pack_bf16(pB0, pB1)));
            sts_f(k.w + 72, F(pack_bf16(pB2, pB3)));
            sts_f(k2.x, (pA0 + pA1) + (pA2 + pA3));
            sts_f(k2.x + 32, (pB0 + pB1) + (pB2 + pB3));
            if (it == 0) {
                if ((t0_ & 31) == 0) mbar_arrive(bars + 8 * MB_KFREE);
                const uint32_t a0 = lds_v4(tb + 4096).z + (SM_V - SM_WQ) + (w >> 2) * 16384;
#pragma unroll
                for (int hf = 0; hf < 4; hf++) {
                    mbar_wait(bars + 8 * (MB_V + hf));
#pragma unroll
                    for (int s = 0; s < 4; s++) ldsm4t(vf[hf * 4 + s], a0 + (hf * 4 + s) * 2048);
                }
            }
            uint4 bc[4];
#pragma unroll
            for (int i = 0; i < 4; i++) bc[i] = lds_v4(sb + SM_ONES);
            TR(8);
            bar_sync<NB_P, 288>();
            float acc[4][4];
#pragma unroll
            for (int i = 0; i < 4; i++) acc[i][0] = acc[i][1] = acc[i][2] = acc[i][3] = 0.f;
#pragma unroll
            for (int i = 0; i < 4; i++) lds_v4_if(bb[i], a_bf + (SM_PS - SM_XS) + i * 256, fl & 2u);
#pragma unroll
            for (int i = 0; i < 4; i++) lds_v4_if(bc[i], a_bf + (SM_PS - SM_XS) + (4 + i) * 256, fl & 2u);
            TR(9);
#pragma unroll
            for (int i = 0; i < 4; i++) {
                mma16816(acc[(2 * i) & 3], vf[2 * i], bb[i].x, bb[i].y);
                mma16816(acc[(2 * i + 1) & 3], vf[2 * i + 1], bb[i].z, bb[i].w);
            }
#pragma unroll
            for (int i = 0; i < 4; i++) {
                mma16816(acc[(2 * i) & 3], vf[8 + 2 * i], bc[i].x, bc[i].y);
                mma16816(acc[(2 * i + 1) & 3], vf[8 + 2 * i + 1], bc[i].z, bc[i].w);
            }
#pragma unroll
            for (int i = 0; i < 4; i++) acc[0][i] = (acc[0][i] + acc[1][i]) + (acc[2][i] + acc[3][i]);
            stx1_if(gs + k.y, acc[0][0], acc[0][2], tag, fl & 16u);
            stx1_if(gs + k.y + 128, acc[0][1], acc[0][3], tag, fl & 16u);
            c_out = clk();
            TR(10);
        }
        {
            const uint4 k = lds_v4(tb + 4096), k4 = lds_v4(tb + 4 * 4096);
            const uint32_t o_c = lds_v4(tb + 3 * 4096).w;
            bool landed = it != 0;
            if (w < 4) {
                uint4 v[4];
                uint2 ml[4];
                float w0, w1, w2, w3;
                if (it == 0) {
                    if (w == 0) prewait<4, 4 * PB>(gs + k4.x + (O_FLV - O_ML), tag); bar_sync<NB_LD, 128>(); }
                int n = 0;
                landed = __all_sync(~0u, mbar_test(bars + 8 * MB_WO));
#pragma unroll 1
                do {
                    wait_until(c_out, DLY_ML);
                    issue<4, 4 * PB>(ml, gs + k4.x);
                    wait_until(c_out, DLY_O);
                    TR(11);
                    issue<4, 4 * PB>(v, gs + o_c);
                    ldw<8>(wf, k.z + (SM_WO - SM_WQ));
                    float M = fmaxf(fmaxf(F(ml[0].y), F(ml[1].y)), fmaxf(F(ml[2].y), F(ml[3].y)));
                    M = fmaxf(M, __shfl_xor_sync(~0u, M, 8));
                    M = fmaxf(M, __shfl_xor_sync(~0u, M, 16));
                    w0 = ex2(F(ml[0].y) - M); w1 = ex2(F(ml[1].y) - M); w2 = ex2(F(ml[2].y) - M); w3 = ex2(F(ml[3].y) - M);
                    float L = fmaf(w0, F(ml[0].x), w1 * F(ml[1].x)) + fmaf(w2, F(ml[2].x), w3 * F(ml[3].x));
                    L += __shfl_xor_sync(~0u, L, 8);
                    L += __shfl_xor_sync(~0u, L, 16);
                    const float inv = rcp(L);
                    w0 *= inv; w1 *= inv; w2 *= inv; w3 *= inv;
                } while (missing2<4>(ml, v, tag + ((w0 + w1) + (w2 + w3) < -1.f ? 1u : 0u)) && ++n < POLL_LIMIT);
                TR(12);
                float4 o;
                o.x = fmaf(w0, F(v[0].x), w1 * F(v[1].x)) + fmaf(w2, F(v[2].x), w3 * F(v[3].x));
                o.y = fmaf(w0, F(v[0].y), w1 * F(v[1].y)) + fmaf(w2, F(v[2].y), w3 * F(v[3].y));
                o.z = fmaf(w0, F(v[0].z), w1 * F(v[1].z)) + fmaf(w2, F(v[2].z), w3 * F(v[3].z));
                o.w = fmaf(w0, F(v[0].w), w1 * F(v[1].w)) + fmaf(w2, F(v[2].w), w3 * F(v[3].w));
                sts_chunk(a_xs + XS_O, ar43(o));
            } else {
                ldw<8>(wf, k.z + (SM_WO - SM_WQ));
            }
            if (!landed) { mbar_wait(bars + 8 * MB_WO); ldw<8>(wf, k.z + (SM_WO - SM_WQ)); }
            bar_sync<NB_B, 256>();
            float d0[4] = {0.f, 0.f, 0.f, 0.f}, d1[4] = {0.f, 0.f, 0.f, 0.f}, d2[4] = {0.f, 0.f, 0.f, 0.f}, d3[4] = {0.f, 0.f, 0.f, 0.f};
#pragma unroll
            for (int i = 0; i < 4; i++) lds_v4_if(bb[i], a_bf + XS_O + i * 256, fl & 1u);
#pragma unroll
            for (int i = 0; i < 4; i += 2) {
                mma16816(d0, wf[2 * i], bb[i].x, bb[i].y);
                mma16816(d1, wf[2 * i + 1], bb[i].z, bb[i].w);
                mma16816(d2, wf[2 * i + 2], bb[i + 1].x, bb[i + 1].y);
                mma16816(d3, wf[2 * i + 3], bb[i + 1].z, bb[i + 1].w);
            }
#pragma unroll
            for (int i = 0; i < 4; i++) d0[i] = (d0[i] + d1[i]) + (d2[i] + d3[i]);
            stx1_if(gs + k.y + (O_RECD - O_RECB), d0[0] + d0[1], d0[2] + d0[3], tag, fl & 4u);
            c_out = clk();
            TR(13);
        }
        {
            const uint4 k = lds_v4(tb + 4 * 4096);
            if (w < 2) {
                float4 xr;
                uint4 v[8];
                wait_until(c_out, DLY_F1);
                if (it == 0) mbar_wait(bars + 8 * MB_W13A);
                TR(14);
                int n = 0;
#pragma unroll 1
                do {
                    issue<8, 16 * PB>(v, gs + k.y);
                    ldw<4>(wf, k.w); ldw<4>(wf + 4, k.w + 16384);
                    bb[0] = lds_v4(sb + SM_ONES);
                    bb[1] = lds_v4(sb + SM_ONES);
                    xr = lds_f4(a_xr + (b0_ & 1) * 256);
                } while (missing<8>(v, tag) && ++n < POLL_LIMIT);
                TR(15);
                float4 x = ar43(sum_v<8>(v));
                x.x += xr.x; x.y += xr.y; x.z += xr.z; x.w += xr.w;
                sts_chunk(a_xs + XS_F1, x);
                sts_v4(a_xr + (SM_XR2 - SM_XR), __float_as_uint(x.x), __float_as_uint(x.y), __float_as_uint(x.z), __float_as_uint(x.w));
            } else {
                ldw<4>(wf, k.w); ldw<4>(wf + 4, k.w + 16384);
                bb[0] = lds_v4(sb + SM_ONES);
                bb[1] = lds_v4(sb + SM_ONES);
            }
            if (it == 0) {
                mbar_wait(bars + 8 * MB_W13A); mbar_wait(bars + 8 * MB_W13);
                ldw<4>(wf, k.w); ldw<4>(wf + 4, k.w + 16384);
            }
            bar_sync<NB_BX, 288>();
            {
                float dg[4] = {0.f, 0.f, 0.f, 0.f}, du[4] = {0.f, 0.f, 0.f, 0.f};
                float dg1[4] = {0.f, 0.f, 0.f, 0.f}, du1[4] = {0.f, 0.f, 0.f, 0.f};
                lds_v4_if(bb[0], a_bf + XS_F1, fl & 1u);
                lds_v4_if(bb[1], a_bf + XS_F1 + 256, fl & 1u);
                mma16816(dg, wf[0], bb[0].x, bb[0].y);
                mma16816(du, wf[4], bb[0].x, bb[0].y);
                mma16816(dg1, wf[1], bb[0].z, bb[0].w);
                mma16816(du1, wf[5], bb[0].z, bb[0].w);
                mma16816(dg, wf[2], bb[1].x, bb[1].y);
                mma16816(du, wf[6], bb[1].x, bb[1].y);
                mma16816(dg1, wf[3], bb[1].z, bb[1].w);
                mma16816(du1, wf[7], bb[1].z, bb[1].w);
                const float h = (fl & 4u) ? 1.f : 0.f;
                const float g0 = fmaf(h, dg[1] + dg1[1], dg[0] + dg1[0]), g1 = fmaf(h, dg[3] + dg1[3], dg[2] + dg1[2]);
                const float u0 = fmaf(h, du[1] + du1[1], du[0] + du1[0]), u1 = fmaf(h, du[3] + du1[3], du[2] + du1[2]);
                stx2_if(gs + k.z, g0, g1, u0, u1, tag, w < 7 ? fl & exp_mask : 0u);
            }
            c_out = clk();
            TR(16);
        }
        {
            const uint4 k = lds_v4(tb + 5 * 4096);
            const uint32_t a0 = lds_v4(tb + 4 * 4096).w + (SM_W2 - SM_W1) - (w >> 2) * 8192;
            bool landed = it != 0;
            float2 xr = make_float2(0.f, 0.f);
            if (b0_ < 8) xr = lds_f2(k.w);
            if (w < 7) {
                const bool b4 = fl & 128u, b3 = fl & 256u;
                const float* pa = gs + k.x;
                const float* ps = gs + ((b0_ & ~7) + ((t0_ >> 3) & 3)) * PB + O_STF;
                uint4 v[2];
                uint2 st[2];
                wait_until(c_out, DLY_F2);
                TR(17);
                const uint32_t a_cs = sb + SM_CSF + t0_ * 8;
                float2 cs = lds_f2(a_cs);
                uint4 cv[2];
                const float* pc = pa + (it == 0 ? O_CSE - O_RECE : 0);
                int n = 0;
                landed = __all_sync(~0u, mbar_test(bars + 8 * MB_W2));
#pragma unroll 1
                do {
                    issue<2, 4 * PB>(st, ps);
                    issue<2, 4 * PB>(v, pa);
                    if (it == 0) issue<2, 4 * PB>(cv, pc); else { cv[0] = make_uint4(tag, 0u, tag, 0u); cv[1] = cv[0]; }
                    ldw<7>(wf, a0);
                } while (missing3(st, v, cv, tag) && ++n < POLL_LIMIT);
                TR(18);
                if (it == 0) {
                    const float4 u = ar43(sum_v<2>(cv));
                    cs.x = b4 ? u.y : u.x;
                    cs.y = b4 ? u.w : u.z;
                    sts_v2(a_cs, __float_as_uint(cs.x), __float_as_uint(cs.y));
                }
                const float4 u0 = sum_v<2>(v);
                float S = F(st[0].x) + F(st[1].x);
                float T = fmaf(fmaf(F(st[0].x), F(st[0].x), F(st[1].x) * F(st[1].x)), 1.f / 64.f, F(st[0].y) + F(st[1].y));
                float G = (b4 ? u0.y : u0.x) + __shfl_xor_sync(~0u, b4 ? u0.x : u0.y, 16);
                float U = (b4 ? u0.w : u0.z) + __shfl_xor_sync(~0u, b4 ? u0.z : u0.w, 16);
                S += __shfl_xor_sync(~0u, S, 16);
                T += __shfl_xor_sync(~0u, T, 16);
                S += __shfl_xor_sync(~0u, S, 8);
                T += __shfl_xor_sync(~0u, T, 8);
                G += __shfl_xor_sync(~0u, G, 8);
                U += __shfl_xor_sync(~0u, U, 8);
                const float mean = S * (1.f / 512.f);
                const float rstd = rsq(fmaxf(fmaf(-mean, mean, T * (1.f / 512.f)), 0.f) + 1e-5f);
                G = rstd * fmaf(-mean, cs.x, G);
                U = rstd * fmaf(-mean, cs.y, U);
                const float hv = G * rcp(1.f + ex2(-1.4426950408889634f * G)) * U;
                const uint32_t hh = pack_bf16(hv, 0.f), ll = pack_bf16(hv - F(hh << 16), 0.f);
                sts_u16(k.z, (uint16_t)(b3 ? ll : hh));
            } else {
                ldw<7>(wf, a0);
            }
            if (!landed) { mbar_wait(bars + 8 * MB_W2); ldw<7>(wf, a0); }
            bar_sync<NB_B, 256>();
            if (w < 4) {
                float d0[4] = {0.f, 0.f, 0.f, 0.f}, d1[4] = {0.f, 0.f, 0.f, 0.f}, d2[4] = {0.f, 0.f, 0.f, 0.f}, d3[4] = {0.f, 0.f, 0.f, 0.f};
#pragma unroll
                for (int i = 0; i < 4; i++) lds_v4_if(bb[i], a_bf + XS_F2 + i * 256, fl & 1u);
                mma16816(d0, wf[0], bb[0].x, bb[0].y);
                mma16816(d1, wf[1], bb[0].z, bb[0].w);
                mma16816(d2, wf[2], bb[1].x, bb[1].y);
                mma16816(d3, wf[3], bb[1].z, bb[1].w);
                mma16816(d0, wf[4], bb[2].x, bb[2].y);
                mma16816(d1, wf[5], bb[2].z, bb[2].w);
                mma16816(d2, wf[6], bb[3].x, bb[3].y);
#pragma unroll
                for (int i = 0; i < 4; i++) d0[i] = (d0[i] + d1[i]) + (d2[i] + d3[i]);
                stx1_if(gs + k.y, (d0[0] + d0[1]) + xr.x, (d0[2] + d0[3]) + xr.y, tag, fl & 4u);
            }
            if (it == 1 && t0_ == 255) sts_f(sb + SM_STOP, 1.f);
            c_out = clk();
            TR(19);
        }
        tagp = tag;
        tag = next_tag(tag);
    }
    if (b0_ == 0 && t0_ == 0) stg_u32(gs + O_EPOCH, ep == 2u ? 0u : ep + 1u);
}

typedef CUresult (*EncodeFn)(CUtensorMap*, CUtensorMapDataType, cuuint32_t, void*, const cuuint64_t*, const cuuint64_t*,
                             const cuuint32_t*, const cuuint32_t*, CUtensorMapInterleave, CUtensorMapSwizzle,
                             CUtensorMapL2promotion, CUtensorMapFloatOOBfill);

void make_map(EncodeFn enc, CUtensorMap* m, const void* p, uint64_t cols, uint64_t rows, uint32_t box_rows) {
    cuuint64_t dims[2] = {cols, rows};
    cuuint64_t strides[1] = {cols * 2};
    cuuint32_t box[2] = {64, box_rows};
    cuuint32_t es[2] = {1, 1};
    enc(m, CU_TENSOR_MAP_DATA_TYPE_BFLOAT16, 2, const_cast<void*>(p), dims, strides, box, es, CU_TENSOR_MAP_INTERLEAVE_NONE,
        CU_TENSOR_MAP_SWIZZLE_128B, CU_TENSOR_MAP_L2_PROMOTION_NONE, CU_TENSOR_MAP_FLOAT_OOB_FILL_NONE);
}

}

extern "C" void kernel_launch(void* const* d_in, const int* in_sizes, int n_in, void* d_out, int out_size) {
    (void)in_sizes; (void)n_in; (void)out_size;
    static EncodeFn enc = nullptr;
    static float* scratch = nullptr;
    if (!enc) {
        void* fn = nullptr;
        cudaDriverEntryPointQueryResult st;
        cudaGetDriverEntryPoint("cuTensorMapEncodeTiled", &fn, cudaEnableDefault, &st);
        enc = (EncodeFn)fn;
        cudaGetSymbolAddress((void**)&scratch, g_s);
        cudaFuncSetAttribute(fused_decode_kernel, cudaFuncAttributeMaxDynamicSharedMemorySize, SM_TOTAL);
    }
    Maps maps;
    make_map(enc, &maps.k, d_in[1], 128, 8ull * SK, 64);
    make_map(enc, &maps.v, d_in[2], 128, 8ull * SK, 64);
    make_map(enc, &maps.wo, d_in[4], 512, 4096, 64);
    make_map(enc, &maps.w1, d_in[6], 1792, 512, 64);
    make_map(enc, &maps.w3, d_in[7], 1792, 512, 64);
    make_map(enc, &maps.w2, d_in[8], 512, 1792, 56);
    fused_decode_kernel<<<NCTA, NTHREADS, SM_TOTAL>>>((const __nv_bfloat16*)d_in[3], scratch, (const __nv_bfloat16*)d_in[0], (__nv_bfloat16*)d_out, maps);
}
```
